```python
import torch

def _softmax(x, axis=-1):
    return torch.softmax(x, dim=axis)
def _gelu(x):
    return torch.nn.functional.gelu(x, approximate="tanh")
def _silu(x):
    return torch.nn.functional.silu(x)
def _sigmoid(x):
    return torch.sigmoid(x)
def _layernorm(x, axis=-1, eps=1e-5):
    m = x.mean(dim=axis, keepdim=True)
    v = x.var(dim=axis, keepdim=True, unbiased=False)
    return (x - m) / torch.sqrt(v + eps)
def _scatter_add(tgt, idx, src, axis=0):
    return tgt.clone().index_add_(axis, idx, src)
def _segment_sum(src, seg, n):
    out = torch.zeros((n,) + src.shape[1:], dtype=src.dtype)
    return out.index_add_(0, seg, src)
def _pad(x, pw):
    flat = tuple(v for pair in reversed(pw) for v in pair)
    return torch.nn.functional.pad(x, flat)

kernel_name = 'concat_heads__gqa_block_cached__mha_block_cached__near_ridge'

def setup_inputs():

    _w = (lambda a: (lambda t: t.to(torch.bfloat16) if t.is_floating_point() else t)(torch.as_tensor(a)))
    def _A_setup():
        B, Sq, D = 16, 48, 512
        Hq, Hkv, Sk, Dh = 32, 8, 512, 128
        assert Hq % Hkv == 0, (Hq, Hkv)
        return {
            "x": _w((lambda *s: torch.randn(*s, dtype=torch.bfloat16) * 0.8)(B, Sq, D)),
            "k_cache": _w((lambda *s: torch.randn(*s, dtype=torch.bfloat16) * 0.8)(B, Hkv, Sk, Dh)),
            "v_cache": _w((lambda *s: torch.randn(*s, dtype=torch.bfloat16) * 0.05)(B, Hkv, Sk, Dh)),
            "wq": _w((lambda *s: torch.randn(*s, dtype=torch.bfloat16) * 0.8)(D, Hq * Dh) * (D ** -0.5)),
            "wo": _w((lambda *s: torch.randn(*s, dtype=torch.bfloat16) * 0.05)(Hq * Dh, D) * ((Hq * Dh) ** -0.5)),
        }
    _A_in = _A_setup()

    def _B_setup():
        B, Sq, D = 16, 48, 512
        H, Sk, Dh = 32, 512, 128
        return {
            "x": _w((lambda *s: torch.randn(*s, dtype=torch.bfloat16) * 0.8)(B, Sq, D)),
            "k_cache": _w((lambda *s: torch.randn(*s, dtype=torch.bfloat16) * 0.8)(B, H, Sk, Dh)),
            "v_cache": _w((lambda *s: torch.randn(*s, dtype=torch.bfloat16) * 0.05)(B, H, Sk, Dh)),
            "wq": _w((lambda *s: torch.randn(*s, dtype=torch.bfloat16) * 0.8)(D, H * Dh) * (D ** -0.5)),
            "wo": _w((lambda *s: torch.randn(*s, dtype=torch.bfloat16) * 0.05)(H * Dh, D) * ((H * Dh) ** -0.5)),
        }
    _B_in = _B_setup()

    return {
        "A_x": _A_in["x"],
        "A_k_cache": _A_in["k_cache"],
        "A_v_cache": _A_in["v_cache"],
        "A_wq": _A_in["wq"],
        "A_wo": _A_in["wo"],
        "B_x": _B_in["x"],
        "B_k_cache": _B_in["k_cache"],
        "B_v_cache": _B_in["v_cache"],
        "B_wq": _B_in["wq"],
        "B_wo": _B_in["wo"],
    }

def reference(A_x, A_k_cache, A_v_cache, A_wq, A_wo, B_x, B_k_cache, B_v_cache, B_wq, B_wo):
    def _A_ref(x, k_cache, v_cache, wq, wo):
        B, Sq, D = x.shape
        Hq, Dh = 32, 128
        Hkv = k_cache.shape[1]
        rep = Hq // Hkv
        q = (lambda x, *d: x.permute(*d))((x @ wq).reshape(B, Sq, Hq, Dh), 0, 2, 1, 3)
        k = (lambda x, n, axis: torch.repeat_interleave(x, n, dim=axis))(k_cache, rep, axis=1)
        v = (lambda x, n, axis: torch.repeat_interleave(x, n, dim=axis))(v_cache, rep, axis=1)
        scores = torch.einsum("bhqd,bhkd->bhqk", q, k) * (Dh ** -0.5)
        p = _softmax(scores, axis=-1)
        o = torch.einsum("bhqk,bhkd->bhqd", p, v)
        return (lambda x, *d: x.permute(*d))(o, 0, 2, 1, 3).reshape(B, Sq, Hq * Dh) @ wo

    def _B_ref(x, k_cache, v_cache, wq, wo):
        B, Sq, D = x.shape
        H, Dh = 32, 128
        q = (lambda x, *d: x.permute(*d))((x @ wq).reshape(B, Sq, H, Dh), 0, 2, 1, 3)
        scores = torch.einsum("bhqd,bhkd->bhqk", q, k_cache) * (Dh ** -0.5)
        p = _softmax(scores, axis=-1)
        o = torch.einsum("bhqk,bhkd->bhqd", p, v_cache)
        return (lambda x, *d: x.permute(*d))(o, 0, 2, 1, 3).reshape(B, Sq, H * Dh) @ wo

    a = _A_ref(A_x, A_k_cache, A_v_cache, A_wq, A_wo)
    b = _B_ref(B_x, B_k_cache, B_v_cache, B_wq, B_wo)
    return torch.concatenate([a, b], axis=-1)
```

```cpp
#include <cuda_runtime.h>
#include <cuda_bf16.h>
#include <cuda.h>
#include <stdint.h>
#include <stdio.h>

namespace mk {

typedef __nv_bfloat16 bf16;

constexpr int NB = 16, SQ = 48, DM = 512, NH = 32, NGRP = 8, SK = 512, DH = 128;
constexpr int SLOT = 16384;
#define NKVS 6
#define NGS 7
#define KV_START_DELAY 0
#define WAIT_HINT_NS 100000u
constexpr int XBYTES = 12288;
constexpr int WREG = 27;
constexpr int SM_KV = 0;
constexpr int SM_QS = NKVS * SLOT;
constexpr int SM_G = SM_QS + 16384;
constexpr int SM_WS = SM_G + NGS * XBYTES;
constexpr int SM_BAR = SM_WS + (32 - WREG) * 4096;
constexpr int SM_TOTAL = SM_BAR + 1024 + 1024;
constexpr int QP_ENTRIES = WREG / 3 + 8 * 4;
constexpr int QPAD = (QP_ENTRIES % NGS + 3 > NGS) ? NGS - QP_ENTRIES % NGS : 0;
constexpr int NCTA = 128;
constexpr int NTHREADS = 512;

constexpr int B_KVF = 0;
constexpr int B_KVE = B_KVF + NKVS;
constexpr int B_GF = B_KVE + NKVS;
constexpr int B_GE = B_GF + NGS;
constexpr int B_EVG = B_GE + NGS;
constexpr int B_EVA = B_EVG + 16;
constexpr int B_WSF = B_EVA + 5;
constexpr int B_WSE = B_WSF + 1;
constexpr int B_RDY = B_WSE + 1;
constexpr int B_END = B_RDY + 21;
static_assert(B_END * 8 + 16 <= 1024, "barrier region");
static_assert(SM_TOTAL <= 232448, "smem");

struct alignas(64) Params {
  CUtensorMap kA, vA, kB, vB;
  CUtensorMap qA, qB;
  CUtensorMap xA, xB, oA, oB;
  CUtensorMap wqA, wqB, woA, woB;
  bf16* out;
  const bf16 *pkA, *pvA, *pkB, *pvB, *pwoA, *pwoB;
};

__device__ bf16 g_QA[NB * NGRP * 192 * DH];
__device__ bf16 g_QB[NB * NH * SQ * DH + 16 * DH];
__device__ bf16 g_OA[NB * SQ * NH * DH];
__device__ bf16 g_OB[NB * SQ * NH * DH];
__device__ float g_part[2 * NB * 4 * 8 * 8 * 768];
struct Flags {
  unsigned epoch;
  unsigned pad0[31];
  unsigned started;
  unsigned pad1[31];
  unsigned qa_cnt[NB * NGRP * 8];
  unsigned qb_flag[NB * NH * 8];
  unsigned oa_cnt[NB * NGRP * 8];
  unsigned ob_cnt[NB * NGRP * 8];
  unsigned part_cnt[2 * NB * 4 * 8];
};
__device__ Flags g_flags;

#define TSTAMP(idx) do {} while (0)

__device__ __forceinline__ uint32_t smem_u32(const void* p) { return (uint32_t)__cvta_generic_to_shared(p); }
__device__ __forceinline__ void mbar_init(uint32_t bar, uint32_t cnt) {
  asm volatile("mbarrier.init.shared::cta.b64 [%0], %1;" ::"r"(bar), "r"(cnt) : "memory");
}
__device__ __forceinline__ void mbar_expect_tx(uint32_t bar, uint32_t bytes) {
  asm volatile("mbarrier.arrive.expect_tx.shared::cta.b64 _, [%0], %1;" ::"r"(bar), "r"(bytes) : "memory");
}
__device__ __forceinline__ void mbar_arrive(uint32_t bar) {
  asm volatile("mbarrier.arrive.shared::cta.b64 _, [%0];" ::"r"(bar) : "memory");
}
__device__ __forceinline__ void mbar_arrive_n(uint32_t bar, uint32_t n) {
  asm volatile("mbarrier.arrive.shared::cta.b64 _, [%0], %1;" ::"r"(bar), "r"(n) : "memory");
}
__device__ __forceinline__ bool mbar_try(uint32_t bar, uint32_t parity) {
  uint32_t ok;
  asm volatile("{\n.reg .pred p;\nmbarrier.try_wait.parity.shared::cta.b64 p, [%1], %2, %3;\nselp.u32 %0, 1, 0, p;\n}"
               : "=r"(ok) : "r"(bar), "r"(parity), "r"(WAIT_HINT_NS) : "memory");
  return ok != 0;
}
__device__ __forceinline__ bool mbar_test(uint32_t bar, uint32_t parity) {
  uint32_t ok;
  asm volatile("{\n.reg .pred p;\nmbarrier.test_wait.parity.shared::cta.b64 p, [%1], %2;\nselp.u32 %0, 1, 0, p;\n}"
               : "=r"(ok) : "r"(bar), "r"(parity) : "memory");
  return ok != 0;
}
__device__ __forceinline__ bool expired(uint32_t bars) {
  uint32_t t0, t1;
  asm volatile("ld.volatile.shared.u32 %0, [%1];" : "=r"(t0) : "r"(bars + B_END * 8 + 8));
  asm volatile("mov.u32 %0, %%clock;" : "=r"(t1));
  return (t1 - t0) > 1900000000u;
}
__device__ __forceinline__ int opaque_tid() {
  int t;
  asm volatile("mov.u32 %0, %%tid.x;" : "=r"(t));
  return t;
}
__device__ __forceinline__ int opaque_cta() {
  int t;
  asm volatile("mov.u32 %0, %%ctaid.x;" : "=r"(t));
  return t;
}
__device__ __forceinline__ void mbar_wait(uint32_t bars, int idx, uint32_t parity) {
  while (!mbar_try(bars + idx * 8, parity)) {
    if (expired(bars)) break;
  }
}
__device__ __forceinline__ unsigned ld_acquire(const unsigned* p) {
  unsigned v;
  asm volatile("ld.acquire.gpu.global.u32 %0, [%1];" : "=r"(v) : "l"(p) : "memory");
  return v;
}
__device__ __forceinline__ void red_add(unsigned* p, unsigned v) {
  asm volatile("red.relaxed.gpu.global.add.u32 [%0], %1;" ::"l"(p), "r"(v) : "memory");
}
__device__ __forceinline__ void wait_flag(uint32_t bars, const unsigned* p, unsigned target) {
  while ((int)(ld_acquire(p) - target) < 0) {
    __nanosleep(64);
    if (expired(bars)) break;
  }
}
__device__ __forceinline__ void fence_proxy_async() { asm volatile("fence.proxy.async.shared::cta;" ::: "memory"); }
__device__ __forceinline__ void fence_proxy_async_global() { asm volatile("fence.proxy.async.global;" ::: "memory"); }
__device__ __forceinline__ void tma_3d(uint32_t dst, const CUtensorMap* map, int c0, int c1, int c2, uint32_t bar) {
  asm volatile(
      "cp.async.bulk.tensor.3d.shared::cluster.global.mbarrier::complete_tx::bytes [%0], [%1, {%3, %4, %5}], [%2];" ::"r"(dst),
      "l"(map), "r"(bar), "r"(c0), "r"(c1), "r"(c2)
      : "memory");
}
__device__ __forceinline__ void bulk_g2s(uint32_t dst, const void* src, uint32_t bytes, uint32_t bar) {
  asm volatile("cp.async.bulk.shared::cluster.global.mbarrier::complete_tx::bytes [%0], [%1], %2, [%3];" ::"r"(dst), "l"(src),
               "r"(bytes), "r"(bar)
               : "memory");
}
__device__ __forceinline__ void touch_page(const void* p) {
  asm volatile("cp.async.bulk.prefetch.L2.global [%0], 16;" ::"l"(p) : "memory");
}
__device__ __forceinline__ void prefetch_tmap(const CUtensorMap* map) {
  asm volatile("prefetch.tensormap [%0];" ::"l"(map) : "memory");
}
__device__ __forceinline__ void ldsm_x4(uint32_t (&r)[4], uint32_t addr) {
  asm volatile("ldmatrix.sync.aligned.m8n8.x4.shared.b16 {%0,%1,%2,%3}, [%4];"
               : "=r"(r[0]), "=r"(r[1]), "=r"(r[2]), "=r"(r[3]) : "r"(addr) : "memory");
}
__device__ __forceinline__ void ldsm_x4_t(uint32_t (&r)[4], uint32_t addr) {
  asm volatile("ldmatrix.sync.aligned.m8n8.x4.trans.shared.b16 {%0,%1,%2,%3}, [%4];"
               : "=r"(r[0]), "=r"(r[1]), "=r"(r[2]), "=r"(r[3]) : "r"(addr) : "memory");
}
__device__ __forceinline__ void stsm_x4_t(uint32_t addr, uint32_t r0, uint32_t r1, uint32_t r2, uint32_t r3) {
  asm volatile("stmatrix.sync.aligned.m8n8.x4.trans.shared.b16 [%0], {%1,%2,%3,%4};" ::"r"(addr), "r"(r0), "r"(r1), "r"(r2),
               "r"(r3)
               : "memory");
}
__constant__ uint32_t c_zero;
__device__ __forceinline__ uint32_t dep_on(uint32_t addr, uint32_t loaded) { return addr + (loaded & c_zero); }
__device__ __forceinline__ void named_bar(int id, int n) { asm volatile("bar.sync %0, %1;" ::"r"(id), "r"(n) : "memory"); }
__device__ __forceinline__ void wg_fence() { asm volatile("wgmma.fence.sync.aligned;" ::: "memory"); }
__device__ __forceinline__ void wg_commit() { asm volatile("wgmma.commit_group.sync.aligned;" ::: "memory"); }
template <int N>
__device__ __forceinline__ void wg_wait() { asm volatile("wgmma.wait_group.sync.aligned %0;" ::"n"(N) : "memory"); }
template <int N>
__device__ __forceinline__ void fence_regs(float (&a)[N]) {
#pragma unroll
  for (int i = 0; i < N; i++) asm volatile("" : "+f"(a[i])::"memory");
}
__device__ __forceinline__ uint64_t make_desc(uint32_t addr, uint32_t lbo, uint32_t sbo) {
  return (uint64_t)((addr & 0x3FFFF) >> 4) | ((uint64_t)(lbo >> 4) << 16) | ((uint64_t)(sbo >> 4) << 32) | (1ull << 62);
}
__device__ __forceinline__ uint32_t pack_bf16(float lo, float hi) {
  uint32_t r;
  asm("cvt.rn.bf16x2.f32 %0, %1, %2;" : "=r"(r) : "f"(hi), "f"(lo));
  return r;
}
__device__ __forceinline__ float ex2(float x) {
  float y;
  asm("ex2.approx.ftz.f32 %0, %1;" : "=f"(y) : "f"(x));
  return y;
}

__device__ __forceinline__ float rcp(float x) {
  float y;
  asm("rcp.approx.ftz.f32 %0, %1;" : "=f"(y) : "f"(x));
  return y;
}

__device__ __forceinline__ void wgmma_n64(float (&d)[32], const uint32_t (&a)[4], uint64_t desc, int scale_d) {
  asm volatile(
      "{\n.reg .pred p;\nsetp.ne.b32 p, %37, 0;\n"
      "wgmma.mma_async.sync.aligned.m64n64k16.f32.bf16.bf16 "
      "{%0,%1,%2,%3,%4,%5,%6,%7,%8,%9,%10,%11,%12,%13,%14,%15,%16,%17,%18,%19,%20,%21,%22,%23,%24,%25,%26,%27,%28,%29,%30,%31},"
      "{%32,%33,%34,%35}, %36, p, 1, 1, 0;\n}"
      : "+f"(d[0]), "+f"(d[1]), "+f"(d[2]), "+f"(d[3]), "+f"(d[4]), "+f"(d[5]), "+f"(d[6]), "+f"(d[7]), "+f"(d[8]), "+f"(d[9]),
        "+f"(d[10]), "+f"(d[11]), "+f"(d[12]), "+f"(d[13]), "+f"(d[14]), "+f"(d[15]), "+f"(d[16]), "+f"(d[17]), "+f"(d[18]),
        "+f"(d[19]), "+f"(d[20]), "+f"(d[21]), "+f"(d[22]), "+f"(d[23]), "+f"(d[24]), "+f"(d[25]), "+f"(d[26]), "+f"(d[27]),
        "+f"(d[28]), "+f"(d[29]), "+f"(d[30]), "+f"(d[31])
      : "r"(a[0]), "r"(a[1]), "r"(a[2]), "r"(a[3]), "l"(desc), "r"(scale_d));
}
__device__ __forceinline__ void wgmma_n64_ss(float (&d)[32], uint64_t da, uint64_t db, int scale_d) {
  asm volatile(
      "{\n.reg .pred p;\nsetp.ne.b32 p, %34, 0;\n"
      "wgmma.mma_async.sync.aligned.m64n64k16.f32.bf16.bf16 "
      "{%0,%1,%2,%3,%4,%5,%6,%7,%8,%9,%10,%11,%12,%13,%14,%15,%16,%17,%18,%19,%20,%21,%22,%23,%24,%25,%26,%27,%28,%29,%30,%31},"
      "%32, %33, p, 1, 1, 0, 0;\n}"
      : "+f"(d[0]), "+f"(d[1]), "+f"(d[2]), "+f"(d[3]), "+f"(d[4]), "+f"(d[5]), "+f"(d[6]), "+f"(d[7]), "+f"(d[8]), "+f"(d[9]),
        "+f"(d[10]), "+f"(d[11]), "+f"(d[12]), "+f"(d[13]), "+f"(d[14]), "+f"(d[15]), "+f"(d[16]), "+f"(d[17]), "+f"(d[18]),
        "+f"(d[19]), "+f"(d[20]), "+f"(d[21]), "+f"(d[22]), "+f"(d[23]), "+f"(d[24]), "+f"(d[25]), "+f"(d[26]), "+f"(d[27]),
        "+f"(d[28]), "+f"(d[29]), "+f"(d[30]), "+f"(d[31])
      : "l"(da), "l"(db), "r"(scale_d));
}
__device__ __forceinline__ void wgmma_n64_t(float (&d)[32], const uint32_t (&a)[4], uint64_t desc, int scale_d) {
  asm volatile(
      "{\n.reg .pred p;\nsetp.ne.b32 p, %37, 0;\n"
      "wgmma.mma_async.sync.aligned.m64n64k16.f32.bf16.bf16 "
      "{%0,%1,%2,%3,%4,%5,%6,%7,%8,%9,%10,%11,%12,%13,%14,%15,%16,%17,%18,%19,%20,%21,%22,%23,%24,%25,%26,%27,%28,%29,%30,%31},"
      "{%32,%33,%34,%35}, %36, p, 1, 1, 1;\n}"
      : "+f"(d[0]), "+f"(d[1]), "+f"(d[2]), "+f"(d[3]), "+f"(d[4]), "+f"(d[5]), "+f"(d[6]), "+f"(d[7]), "+f"(d[8]), "+f"(d[9]),
        "+f"(d[10]), "+f"(d[11]), "+f"(d[12]), "+f"(d[13]), "+f"(d[14]), "+f"(d[15]), "+f"(d[16]), "+f"(d[17]), "+f"(d[18]),
        "+f"(d[19]), "+f"(d[20]), "+f"(d[21]), "+f"(d[22]), "+f"(d[23]), "+f"(d[24]), "+f"(d[25]), "+f"(d[26]), "+f"(d[27]),
        "+f"(d[28]), "+f"(d[29]), "+f"(d[30]), "+f"(d[31])
      : "r"(a[0]), "r"(a[1]), "r"(a[2]), "r"(a[3]), "l"(desc), "r"(scale_d));
}
__device__ __forceinline__ void wgmma_n32(float (&d)[16], const uint32_t (&a)[4], uint64_t desc, int scale_d) {
  asm volatile(
      "{\n.reg .pred p;\nsetp.ne.b32 p, %21, 0;\n"
      "wgmma.mma_async.sync.aligned.m64n32k16.f32.bf16.bf16 "
      "{%0,%1,%2,%3,%4,%5,%6,%7,%8,%9,%10,%11,%12,%13,%14,%15},"
      "{%16,%17,%18,%19}, %20, p, 1, 1, 0;\n}"
      : "+f"(d[0]), "+f"(d[1]), "+f"(d[2]), "+f"(d[3]), "+f"(d[4]), "+f"(d[5]), "+f"(d[6]), "+f"(d[7]), "+f"(d[8]), "+f"(d[9]),
        "+f"(d[10]), "+f"(d[11]), "+f"(d[12]), "+f"(d[13]), "+f"(d[14]), "+f"(d[15])
      : "r"(a[0]), "r"(a[1]), "r"(a[2]), "r"(a[3]), "l"(desc), "r"(scale_d));
}
__device__ __forceinline__ void wgmma_n128_t(float (&d)[64], const uint32_t (&a)[4], uint64_t desc, int scale_d) {
  asm volatile(
      "{\n.reg .pred p;\nsetp.ne.b32 p, %69, 0;\n"
      "wgmma.mma_async.sync.aligned.m64n128k16.f32.bf16.bf16 "
      "{%0,%1,%2,%3,%4,%5,%6,%7,%8,%9,%10,%11,%12,%13,%14,%15,%16,%17,%18,%19,%20,%21,%22,%23,%24,%25,%26,%27,%28,%29,%30,%31,"
      "%32,%33,%34,%35,%36,%37,%38,%39,%40,%41,%42,%43,%44,%45,%46,%47,%48,%49,%50,%51,%52,%53,%54,%55,%56,%57,%58,%59,%60,%61,%62,%63},"
      "{%64,%65,%66,%67}, %68, p, 1, 1, 1;\n}"
      : "+f"(d[0]), "+f"(d[1]), "+f"(d[2]), "+f"(d[3]), "+f"(d[4]), "+f"(d[5]), "+f"(d[6]), "+f"(d[7]), "+f"(d[8]), "+f"(d[9]),
        "+f"(d[10]), "+f"(d[11]), "+f"(d[12]), "+f"(d[13]), "+f"(d[14]), "+f"(d[15]), "+f"(d[16]), "+f"(d[17]), "+f"(d[18]),
        "+f"(d[19]), "+f"(d[20]), "+f"(d[21]), "+f"(d[22]), "+f"(d[23]), "+f"(d[24]), "+f"(d[25]), "+f"(d[26]), "+f"(d[27]),
        "+f"(d[28]), "+f"(d[29]), "+f"(d[30]), "+f"(d[31]), "+f"(d[32]), "+f"(d[33]), "+f"(d[34]), "+f"(d[35]), "+f"(d[36]),
        "+f"(d[37]), "+f"(d[38]), "+f"(d[39]), "+f"(d[40]), "+f"(d[41]), "+f"(d[42]), "+f"(d[43]), "+f"(d[44]), "+f"(d[45]),
        "+f"(d[46]), "+f"(d[47]), "+f"(d[48]), "+f"(d[49]), "+f"(d[50]), "+f"(d[51]), "+f"(d[52]), "+f"(d[53]), "+f"(d[54]),
        "+f"(d[55]), "+f"(d[56]), "+f"(d[57]), "+f"(d[58]), "+f"(d[59]), "+f"(d[60]), "+f"(d[61]), "+f"(d[62]), "+f"(d[63])
      : "r"(a[0]), "r"(a[1]), "r"(a[2]), "r"(a[3]), "l"(desc), "r"(scale_d));
}
__device__ __forceinline__ void wgmma_n48(float (&d)[24], const uint32_t (&a)[4], uint64_t desc, int scale_d) {
  asm volatile(
      "{\n.reg .pred p;\nsetp.ne.b32 p, %29, 0;\n"
      "wgmma.mma_async.sync.aligned.m64n48k16.f32.bf16.bf16 "
      "{%0,%1,%2,%3,%4,%5,%6,%7,%8,%9,%10,%11,%12,%13,%14,%15,%16,%17,%18,%19,%20,%21,%22,%23},"
      "{%24,%25,%26,%27}, %28, p, 1, 1, 0;\n}"
      : "+f"(d[0]), "+f"(d[1]), "+f"(d[2]), "+f"(d[3]), "+f"(d[4]), "+f"(d[5]), "+f"(d[6]), "+f"(d[7]), "+f"(d[8]), "+f"(d[9]),
        "+f"(d[10]), "+f"(d[11]), "+f"(d[12]), "+f"(d[13]), "+f"(d[14]), "+f"(d[15]), "+f"(d[16]), "+f"(d[17]), "+f"(d[18]),
        "+f"(d[19]), "+f"(d[20]), "+f"(d[21]), "+f"(d[22]), "+f"(d[23])
      : "r"(a[0]), "r"(a[1]), "r"(a[2]), "r"(a[3]), "l"(desc), "r"(scale_d));
}

__device__ __forceinline__ void wgmma_n48_ss(float (&d)[24], uint64_t descA, uint64_t descB) {
  asm volatile(
      "{\n.reg .pred p;\nsetp.ne.b32 p, 1, 0;\n"
      "wgmma.mma_async.sync.aligned.m64n48k16.f32.bf16.bf16 "
      "{%0,%1,%2,%3,%4,%5,%6,%7,%8,%9,%10,%11,%12,%13,%14,%15,%16,%17,%18,%19,%20,%21,%22,%23},"
      "%24, %25, p, 1, 1, 1, 0;\n}"
      : "+f"(d[0]), "+f"(d[1]), "+f"(d[2]), "+f"(d[3]), "+f"(d[4]), "+f"(d[5]), "+f"(d[6]), "+f"(d[7]), "+f"(d[8]), "+f"(d[9]),
        "+f"(d[10]), "+f"(d[11]), "+f"(d[12]), "+f"(d[13]), "+f"(d[14]), "+f"(d[15]), "+f"(d[16]), "+f"(d[17]), "+f"(d[18]),
        "+f"(d[19]), "+f"(d[20]), "+f"(d[21]), "+f"(d[22]), "+f"(d[23])
      : "l"(descA), "l"(descB));
}
__device__ __forceinline__ uint32_t movmatrix_t(uint32_t x) {
  uint32_t y;
  asm volatile("movmatrix.sync.aligned.m8n8.trans.b16 %0, %1;" : "=r"(y) : "r"(x));
  return y;
}

template <int N>
struct Cursor {
  int slot;
  uint32_t phase;
  __device__ __forceinline__ void init(int count) { slot = count % N; phase = (count / N) & 1; }
  __device__ __forceinline__ void next() { if (++slot == N) { slot = 0; phase ^= 1; } }
};

constexpr float SM_C = 0.08838834764831845f * 1.4426950408889634f;
constexpr float RESCALE_T = 8.0f;

template <int NS>
__device__ __forceinline__ void softmax_step(const float (&s)[NS], uint32_t (&pf)[NS / 8][4], float (&o)[64],
                                             float& m0, float& m1, float& l0, float& l1, bool first) {
  float mx0 = fmaxf(s[0], s[1]), mx1 = fmaxf(s[2], s[3]);
#pragma unroll
  for (int j = 1; j < NS / 4; j++) {
    mx0 = fmaxf(mx0, fmaxf(s[4 * j], s[4 * j + 1]));
    mx1 = fmaxf(mx1, fmaxf(s[4 * j + 2], s[4 * j + 3]));
  }
  mx0 = fmaxf(mx0, __shfl_xor_sync(0xffffffffu, mx0, 1));
  mx1 = fmaxf(mx1, __shfl_xor_sync(0xffffffffu, mx1, 1));
  mx0 = fmaxf(mx0, __shfl_xor_sync(0xffffffffu, mx0, 2));
  mx1 = fmaxf(mx1, __shfl_xor_sync(0xffffffffu, mx1, 2));
  const bool grow = !((mx0 - m0) * SM_C <= RESCALE_T) || !((mx1 - m1) * SM_C <= RESCALE_T);
  if (__any_sync(0xffffffffu, grow)) {
    const float mn0 = fmaxf(m0, mx0), mn1 = fmaxf(m1, mx1);
    const float a0 = ex2((m0 - mn0) * SM_C), a1 = ex2((m1 - mn1) * SM_C);
    m0 = mn0; m1 = mn1;
    l0 *= a0; l1 *= a1;
    if (!first) {
#pragma unroll
      for (int j = 0; j < 16; j++) {
        o[4 * j] *= a0; o[4 * j + 1] *= a0; o[4 * j + 2] *= a1; o[4 * j + 3] *= a1;
      }
    }
  }
  const float mc0 = m0 * SM_C, mc1 = m1 * SM_C;
#pragma unroll
  for (int j = 0; j < NS / 4; j++) {
    const float p0 = ex2(fmaf(s[4 * j], SM_C, -mc0)), p1 = ex2(fmaf(s[4 * j + 1], SM_C, -mc0));
    const float p2 = ex2(fmaf(s[4 * j + 2], SM_C, -mc1)), p3 = ex2(fmaf(s[4 * j + 3], SM_C, -mc1));
    l0 += p0 + p1; l1 += p2 + p3;
    pf[j >> 1][(j & 1) * 2 + 0] = pack_bf16(p0, p1);
    pf[j >> 1][(j & 1) * 2 + 1] = pack_bf16(p2, p3);
  }
}

template <bool isA>
__device__ __forceinline__ void attn_epilogue(const float (&o)[64], float l0, float l1, int slotB) {
  l0 += __shfl_xor_sync(0xffffffffu, l0, 1); l1 += __shfl_xor_sync(0xffffffffu, l1, 1);
  l0 += __shfl_xor_sync(0xffffffffu, l0, 2); l1 += __shfl_xor_sync(0xffffffffu, l1, 2);
  const float i0 = rcp(l0), i1 = rcp(l1);
  const int tid = opaque_tid(), cta = opaque_cta();
  const int h = cta >> 2, jg = cta & 3;
  const int r0 = (tid >> 5) * 16 + ((tid & 31) >> 2), r1 = r0 + 8;
  bf16 *orow0, *orow1;
  if (isA) {
    const int bA = 4 * jg + (h & 3);
    orow0 = g_OA + (size_t)(bA * SQ + r0 % SQ) * 4096 + ((h >> 2) * 4 + r0 / SQ) * DH;
    orow1 = g_OA + (size_t)(bA * SQ + r1 % SQ) * 4096 + ((h >> 2) * 4 + r1 / SQ) * DH;
  } else {
    orow0 = g_OB + (size_t)((4 * jg + slotB) * SQ + r0) * 4096 + h * DH;
    orow1 = orow0 + 8 * 4096;
  }
  const int cq = (tid & 3) * 2;
#pragma unroll
  for (int j = 0; j < 16; j++) {
    *reinterpret_cast<uint32_t*>(orow0 + j * 8 + cq) = pack_bf16(o[4 * j] * i0, o[4 * j + 1] * i0);
    *reinterpret_cast<uint32_t*>(orow1 + j * 8 + cq) = pack_bf16(o[4 * j + 2] * i1, o[4 * j + 3] * i1);
  }
}

template <bool isA, bool isWG0>
__device__ __forceinline__ void attn_ss(uint32_t sm, uint32_t bars, Cursor<NKVS>& cur, int slotB, uint32_t qs) {
  const int tid_ = opaque_tid();
  const bool leader = (tid_ & 31) == 0;
  constexpr uint32_t narr = isA ? 1 : 3;
  const bool active = isA || (tid_ >> 5) < 3;
  if (isWG0) {
    mbar_wait(bars, B_KVF + cur.slot, cur.phase);
    const uint32_t src = sm + SM_KV + cur.slot * SLOT + tid_ * 16, dst = qs + tid_ * 16;
    uint32_t x = 0;
#pragma unroll
    for (int i = 0; i < 8; i++) {
      uint4 v;
      asm volatile("ld.shared.v4.u32 {%0,%1,%2,%3}, [%4];" : "=r"(v.x), "=r"(v.y), "=r"(v.z), "=r"(v.w) : "r"(src + i * 2048) : "memory");
      asm volatile("st.shared.v4.u32 [%0], {%1,%2,%3,%4};" ::"r"(dst + i * 2048), "r"(v.x), "r"(v.y), "r"(v.z), "r"(v.w) : "memory");
      x ^= v.x;
    }
    const uint32_t rel = dep_on(bars + (B_KVE + cur.slot) * 8, x);
    __syncwarp();
    if (leader) mbar_arrive_n(rel, narr);
    cur.next();
    fence_proxy_async();
    named_bar(1, 128);
  } else {
    mbar_wait(bars, B_KVF + cur.slot, cur.phase);
    if (leader) mbar_arrive(bars + (B_KVE + cur.slot) * 8);
    cur.next();
  }
  float o[64];
  float s[32];
  float m0 = -INFINITY, m1 = -INFINITY, l0 = 0.f, l1 = 0.f;
  mbar_wait(bars, B_KVF + cur.slot, cur.phase);
  wg_fence();
#pragma unroll
  for (int ks = 0; ks < 8; ks++)
    wgmma_n64_ss(s, make_desc(qs + (ks >> 2) * 8192 + (ks & 3) * 32, 16, 1024),
                 make_desc(sm + SM_KV + cur.slot * SLOT + (ks >> 2) * 8192 + (ks & 3) * 32, 16, 1024), ks > 0);
  wg_commit();
  wg_wait<0>();
  fence_regs(s);
  if (leader) mbar_arrive_n(bars + (B_KVE + cur.slot) * 8, narr);
  cur.next();
#pragma unroll 1
  for (int t = 0; t < 8; t++) {
    uint32_t pf[4][4];
    if (active) softmax_step<32>(s, pf, o, m0, m1, l0, l1, t == 0);
    else {
#pragma unroll
      for (int k = 0; k < 4; k++) { pf[k][0] = 0; pf[k][1] = 0; pf[k][2] = 0; pf[k][3] = 0; }
    }
    const int vs = cur.slot; const uint32_t vp = cur.phase; cur.next();
    mbar_wait(bars, B_KVF + vs, vp);
    wg_fence();
#pragma unroll
    for (int kk = 0; kk < 4; kk++)
      wgmma_n128_t(o, pf[kk], make_desc(sm + SM_KV + vs * SLOT + kk * 2048, 8192, 1024), (t > 0) || (kk > 0));
    wg_commit();
    if (t < 7) {
      const int ks_ = cur.slot;
      mbar_wait(bars, B_KVF + ks_, cur.phase);
      cur.next();
      wg_fence();
#pragma unroll
      for (int ks = 0; ks < 8; ks++)
        wgmma_n64_ss(s, make_desc(qs + (ks >> 2) * 8192 + (ks & 3) * 32, 16, 1024),
                     make_desc(sm + SM_KV + ks_ * SLOT + (ks >> 2) * 8192 + (ks & 3) * 32, 16, 1024), ks > 0);
      wg_commit();
      wg_wait<1>();
      if (leader) mbar_arrive_n(bars + (B_KVE + vs) * 8, narr);
      wg_wait<0>();
      if (leader) mbar_arrive_n(bars + (B_KVE + ks_) * 8, narr);
    } else {
      wg_wait<0>();
      if (leader) mbar_arrive_n(bars + (B_KVE + vs) * 8, narr);
    }
    fence_regs(s); fence_regs(o);
  }
  if (active) attn_epilogue<isA>(o, l0, l1, slotB);
}

__device__ __forceinline__ void signal_unit(uint32_t bars, int u) {
  __syncwarp();
  if ((opaque_tid() & 31) == 0) mbar_arrive(bars + (B_EVA + u) * 8);
}

__device__ __forceinline__ void load_w(uint32_t (&wf)[WREG][4], uint32_t sm_g, uint32_t bars, Cursor<NGS>& cur) {
  const int tid = opaque_tid();
  const int lane = tid & 31, warp = (tid >> 5) & 3, half = (tid >> 7) - 1;
  const int mi = lane >> 3, rr = lane & 7;
  const int chunk = warp * 2 + (mi & 1);
  const uint32_t off = sm_g + half * 2048 + ((mi >> 1) * 8 + rr) * 128 + ((chunk ^ rr) << 4);
#pragma unroll
  for (int c = 0; c < WREG / 3; c++) {
    mbar_wait(bars, B_GF + cur.slot, cur.phase);
    const uint32_t base = off + cur.slot * XBYTES;
#pragma unroll
    for (int ks = 0; ks < 3; ks++) ldsm_x4_t(wf[c * 3 + ks], base + ks * 4096);
    const uint32_t rel = dep_on(bars + (B_GE + cur.slot) * 8, wf[c * 3][0] ^ wf[c * 3 + 1][0] ^ wf[c * 3 + 2][0]);
    __syncwarp();
    if (lane == 0) mbar_arrive(rel);
    cur.next();
  }
}

__device__ __forceinline__ void brick(float (&acc)[24], const uint32_t (&wf)[WREG][4], uint32_t sm_g, uint32_t sm_ws, uint32_t bars,
                                      Cursor<NGS>& cur) {
  int prev_slot = 0;
  const int tid = opaque_tid();
  const bool leader = (tid & 31) == 0;
  const uint32_t ws = sm_ws + ((tid >> 7) - 1) * 2048;
#pragma unroll
  for (int i = 0; i < 4; i++) {
    mbar_wait(bars, B_GF + cur.slot, cur.phase);
    const uint32_t base = sm_g + cur.slot * XBYTES;
    wg_fence();
#pragma unroll
    for (int ks = 0; ks < 8; ks++) {
      const uint64_t db = make_desc(base + (ks >> 2) * 6144 + (ks & 3) * 32, 16, 1024);
      if (i * 8 + ks < WREG) wgmma_n48(acc, wf[i * 8 + ks], db, (i > 0) || (ks > 0));
      else wgmma_n48_ss(acc, make_desc(ws + (i * 8 + ks - WREG) * 4096, 8192, 1024), db);
    }
    wg_commit();
    if (i > 0) {
      wg_wait<1>();
      if (leader) mbar_arrive(bars + (B_GE + prev_slot) * 8);
    }
    prev_slot = cur.slot;
    cur.next();
  }
  wg_wait<0>();
  fence_regs(acc);
  if (leader) mbar_arrive(bars + (B_GE + prev_slot) * 8);
}

__device__ __forceinline__ int qp_batch(int j, int i) { return 8 * (j & 1) + (i >> 1) + 4 * (i & 1); }
__device__ __forceinline__ void epi_q(const float (&acc)[24], int i) {
  const int tid = opaque_tid(), cta = opaque_cta();
  const int lane = tid & 31, w8 = (tid >> 5) - 4;
  const int h = cta >> 2, j = cta & 3, b = qp_batch(j, i);
  bf16* dst = (j < 2) ? g_QB + (size_t)((b * NH + h) * SQ) * DH : g_QA + (size_t)((b * NGRP + (h >> 2)) * 192 + (h & 3) * SQ) * DH;
  bf16* p = dst + w8 * 16 + (lane >> 2) * 128 + (lane & 3) * 2;
#pragma unroll
  for (int jb = 0; jb < 6; jb++) {
    const uint32_t lo = movmatrix_t(pack_bf16(acc[4 * jb + 0], acc[4 * jb + 1]));
    const uint32_t hi = movmatrix_t(pack_bf16(acc[4 * jb + 2], acc[4 * jb + 3]));
    *reinterpret_cast<uint32_t*>(p + jb * 8 * 128) = lo;
    *reinterpret_cast<uint32_t*>(p + jb * 8 * 128 + 8) = hi;
  }
}
__device__ __forceinline__ void epi_part(const float (&acc)[24], int br, int s) {
  const int tid = opaque_tid(), cta = opaque_cta();
  const int lane = tid & 31, w8 = (tid >> 5) - 4;
  const int h = cta >> 2, b = 4 * (cta & 3) + s;
  float* dst = g_part + ((size_t)(((br * NB + b) * 4 + (h & 3)) * 8 + w8)) * (8 * 768) + (h >> 2) * 768 + lane * 4;
#pragma unroll
  for (int i = 0; i < 6; i++)
    *reinterpret_cast<float4*>(dst + i * 128) = make_float4(acc[4 * i], acc[4 * i + 1], acc[4 * i + 2], acc[4 * i + 3]);
}

__device__ __forceinline__ void finalize(uint32_t sm_g, uint32_t bars, Cursor<NGS>& cur, bf16* out, int br, int q) {
  const int tid = opaque_tid(), cta = opaque_cta();
  const int t256 = tid - 128;
  const int h = cta >> 2;
  bf16* dst = out + (size_t)((4 * (cta & 3) + q) * SQ) * 1024 + br * 512 + (h & 3) * 128 + (h >> 2) * 16;
  const int s0_ = cur.slot; const uint32_t p0_ = cur.phase; cur.next();
  const int s1_ = cur.slot; const uint32_t p1_ = cur.phase; cur.next();
  mbar_wait(bars, B_GF + s0_, p0_);
  mbar_wait(bars, B_GF + s1_, p1_);
  const uint32_t b0 = sm_g + s0_ * XBYTES, b1 = sm_g + s1_ * XBYTES;
#pragma unroll 1
  for (int item = t256; item < 384; item += 256) {
    const int r = item >> 3, c = (item & 7) * 2;
    const int f0 = (((r >> 3) * 32 + (c & 7) * 4 + ((r & 7) >> 1)) * 4 + (c >> 3) * 2 + (r & 1)) * 4;
    float s0 = 0.f, s1 = 0.f;
#pragma unroll
    for (int p = 0; p < 8; p++) {
      const uint32_t a = (p < 4 ? b0 : b1) + (p & 3) * 3072 + f0;
      float x0, x1;
      asm volatile("ld.shared.f32 %0, [%1];" : "=f"(x0) : "r"(a));
      asm volatile("ld.shared.f32 %0, [%1+64];" : "=f"(x1) : "r"(a));
      s0 += x0; s1 += x1;
    }
    *reinterpret_cast<uint32_t*>(dst + r * 1024 + c) = pack_bf16(s0, s1);
  }
  __syncwarp();
  if ((tid & 31) == 0) {
    mbar_arrive(bars + (B_GE + s0_) * 8);
    mbar_arrive(bars + (B_GE + s1_) * 8);
  }
}

__device__ __forceinline__ void gemm_qp(uint32_t sm, uint32_t bars, Cursor<NGS>& gc) {
  uint32_t wf[WREG][4];
  if (threadIdx.x == 128) TSTAMP(16);
  load_w(wf, sm + SM_G, bars, gc);
  mbar_wait(bars, B_WSF, 0);
#pragma unroll 1
  for (int i = 0; i < 8; i++) {
    float acc[24];
    brick(acc, wf, sm + SM_G, sm + SM_WS, bars, gc);
    const bool leader = (opaque_tid() & 31) == 0;
    if (i == 7 && leader) mbar_arrive(bars + B_WSE * 8);
    epi_q(acc, i);
    __syncwarp();
    if (leader) mbar_arrive(bars + (B_EVG + i) * 8);
    if (threadIdx.x == 128) TSTAMP(17 + i);
  }
}
__device__ __forceinline__ void gemm_op(uint32_t sm, uint32_t bars, Cursor<NGS>& gc, bf16* out) {
#pragma unroll 1
  for (int br = 0; br < 2; br++) {
    uint32_t wf[WREG][4];
    if (threadIdx.x == 128) TSTAMP(32 + br * 8);
    load_w(wf, sm + SM_G, bars, gc);
    mbar_wait(bars, B_WSF, (br + 1) & 1);
#pragma unroll 1
    for (int s = 0; s < 4; s++) {
      float acc[24];
      brick(acc, wf, sm + SM_G, sm + SM_WS, bars, gc);
      const bool leader = (opaque_tid() & 31) == 0;
      if (s == 3 && leader) mbar_arrive(bars + B_WSE * 8);
      epi_part(acc, br, s);
      __syncwarp();
      if (leader) mbar_arrive(bars + (B_EVG + 8 + br * 4 + s) * 8);
      if (threadIdx.x == 128) TSTAMP(33 + br * 8 + s);
      if (br == 1) {
        const int nf = (s == 0) ? 4 : (s == 2 ? 2 : 1);
#pragma unroll 1
        for (int f = 0; f < nf; f++) {
          const int fb = (s == 0) ? 0 : 1;
          const int q = (s == 0) ? f : (s == 1 ? 0 : (s == 2 ? 1 + f : 3));
          finalize(sm + SM_G, bars, gc, out, fb, q);
        }
      }
    }
  }
}

__global__ void __launch_bounds__(NTHREADS, 1) fused_kernel(const __grid_constant__ Params P) {
  extern __shared__ uint8_t smem_raw[];
  const uint32_t sm = (smem_u32(smem_raw) + 1023u) & ~1023u;
  const uint32_t bars = sm + SM_BAR;
  volatile unsigned* s_epoch = reinterpret_cast<volatile unsigned*>(smem_raw + (sm - smem_u32(smem_raw)) + SM_BAR + B_END * 8);
  const int tid = threadIdx.x, wg = tid >> 7, warp = (tid >> 5) & 3, lane = tid & 31;
  const int cta = blockIdx.x;
  const int h = cta >> 2, j = cta & 3;
  const int n_t = h & 3, kc = h >> 2;

  if (tid == 0) {
    TSTAMP(0);
    for (int i = 0; i < NKVS; i++) { mbar_init(bars + (B_KVF + i) * 8, 1); mbar_init(bars + (B_KVE + i) * 8, 12); }
    for (int i = 0; i < NGS; i++) { mbar_init(bars + (B_GF + i) * 8, 1); mbar_init(bars + (B_GE + i) * 8, 8); }
    for (int i = 0; i < 16; i++) mbar_init(bars + (B_EVG + i) * 8, 8);
    for (int i = 0; i < 5; i++) mbar_init(bars + (B_EVA + i) * 8, i == 1 ? 12 : 4);
    mbar_init(bars + B_WSF * 8, 1);
    mbar_init(bars + B_WSE * 8, 8);
    for (int i = 0; i < 21; i++) mbar_init(bars + (B_RDY + i) * 8, 1);
    asm volatile("st.shared.u32 [%0], %1;" ::"r"(bars + B_END * 8 + 8), "r"((uint32_t)clock()) : "memory");
    asm volatile("fence.mbarrier_init.release.cluster;" ::: "memory");
    const unsigned e = *reinterpret_cast<volatile unsigned*>(&g_flags.epoch);
    *s_epoch = e;
    __threadfence();
    const unsigned old = atomicAdd(&g_flags.started, 1u);
    if (old == gridDim.x - 1) {
      g_flags.started = 0;
      __threadfence();
      *reinterpret_cast<volatile unsigned*>(&g_flags.epoch) = e + 1;
    }
  }
  __syncthreads();
  const unsigned ep1 = *s_epoch + 1;

  if (wg == 3) {
    asm volatile("setmaxnreg.dec.sync.aligned.u32 32;");
    if (warp == 0 && lane == 0) {
      prefetch_tmap(&P.kB); prefetch_tmap(&P.vB); prefetch_tmap(&P.qB);
      prefetch_tmap(&P.kA); prefetch_tmap(&P.vA); prefetch_tmap(&P.qA);
      for (int u = 0; u < 5; u++) {
        const bool isA = (u == 1);
        const int s = u == 0 ? 0 : u - 1;
        const size_t off = isA ? (size_t)((4 * j + (h & 3)) * NGRP + kc) * SK * DH : (size_t)((4 * j + s) * NH + h) * SK * DH;
        touch_page((isA ? P.pkA : P.pkB) + off);
        touch_page((isA ? P.pvA : P.pvB) + off);
      }
      if (KV_START_DELAY > 0) __nanosleep(KV_START_DELAY);
      Cursor<NKVS> c; c.init(0);
#pragma unroll 1
      for (int u = 0; u < 5; u++) {
        const bool isA = (u == 1);
        const int s = u == 0 ? 0 : u - 1;
        const int b = isA ? 4 * j + (h & 3) : 4 * j + s;
        const int nq = 1;
        const CUtensorMap* mk_ = isA ? &P.kA : &P.kB;
        const CUtensorMap* mv_ = isA ? &P.vA : &P.vB;
        const CUtensorMap* mq_ = isA ? &P.qA : &P.qB;
        const int row0 = isA ? (b * NGRP + kc) * SK : (b * NH + h) * SK;
        const int qrow0 = isA ? (b * NGRP + kc) * 192 : (b * NH + h) * SQ;
        Cursor<NKVS> qc = c;
        for (int i = 0; i < nq; i++) { mbar_wait(bars, B_KVE + c.slot, c.phase ^ 1); c.next(); }
        bool qdone = false;
#pragma unroll 1
        for (int t = 0; t < 16; t++) {
          if (!qdone) {
            while (true) {
              if (mbar_test(bars + (B_RDY + u) * 8, 0)) {
                for (int i = 0; i < nq; i++) {
                  mbar_expect_tx(bars + (B_KVF + qc.slot) * 8, SLOT);
                  tma_3d(sm + SM_KV + qc.slot * SLOT, mq_, 0, qrow0 + i * 64, 0, bars + (B_KVF + qc.slot) * 8);
                  qc.next();
                }
                qdone = true;
                break;
              }
              if (mbar_test(bars + (B_KVE + c.slot) * 8, c.phase ^ 1)) break;
              if (expired(bars)) break;
              __nanosleep(100);
            }
          }
          mbar_wait(bars, B_KVE + c.slot, c.phase ^ 1);
          mbar_expect_tx(bars + (B_KVF + c.slot) * 8, SLOT);
          tma_3d(sm + SM_KV + c.slot * SLOT, (t & 1) ? mv_ : mk_, 0, row0 + (t >> 1) * 64, 0, bars + (B_KVF + c.slot) * 8);
          c.next();
        }
      }
    } else if (warp == 1 && lane == 0) {
      prefetch_tmap(&P.wqB); prefetch_tmap(&P.xB); prefetch_tmap(&P.wqA); prefetch_tmap(&P.xA);
      prefetch_tmap(&P.woA); prefetch_tmap(&P.oA); prefetch_tmap(&P.woB); prefetch_tmap(&P.oB);
      touch_page(P.pwoA + (size_t)kc * 512 * 512);
      touch_page(P.pwoB + (size_t)kc * 512 * 512);
      touch_page(g_OA + (size_t)(4 * j * SQ) * 4096);
      touch_page(g_OB + (size_t)(4 * j * SQ) * 4096);
      touch_page(g_OA + (size_t)((4 * j + 3) * SQ + 47) * 4096);
      touch_page(g_OB + (size_t)((4 * j + 3) * SQ + 47) * 4096);
      for (int q = 0; q < 8; q++) touch_page(g_part + ((size_t)((((q >> 2) * NB + 4 * j + (q & 3)) * 4 + n_t) * 8 + kc)) * (8 * 768));
      Cursor<NGS> c; c.init(0);
      uint32_t wsph = 1;
      auto ldW = [&](const CUtensorMap* m, int k0, int nch) {
        for (int i = 0; i < WREG / 3; i++) {
          mbar_wait(bars, B_GE + c.slot, c.phase ^ 1);
          mbar_expect_tx(bars + (B_GF + c.slot) * 8, XBYTES);
          for (int q = 0; q < 3; q++)
            tma_3d(sm + SM_G + c.slot * XBYTES + q * 4096, m, 0, k0 + (i * 3 + q) * 16, nch, bars + (B_GF + c.slot) * 8);
          c.next();
        }
        mbar_wait(bars, B_WSE, wsph);
        wsph ^= 1;
        mbar_expect_tx(bars + B_WSF * 8, (32 - WREG) * 4096);
        for (int q = 0; q < 32 - WREG; q++)
          tma_3d(sm + SM_WS + q * 4096, m, 0, k0 + (WREG + q) * 16, nch, bars + B_WSF * 8);
      };
      auto ldX = [&](const CUtensorMap* m, int row0, int ch0) {
        for (int i = 0; i < 4; i++) {
          mbar_wait(bars, B_GE + c.slot, c.phase ^ 1);
          mbar_expect_tx(bars + (B_GF + c.slot) * 8, XBYTES);
          tma_3d(sm + SM_G + c.slot * XBYTES, m, 0, row0, ch0 + 2 * i, bars + (B_GF + c.slot) * 8);
          c.next();
        }
      };
      auto ldF = [&](int br, int s) {
        const int b = 4 * j + s;
        mbar_wait(bars, B_RDY + 13 + br * 4 + s, 0);
        const float* src = g_part + ((size_t)(((br * NB + b) * 4 + n_t) * 8 + kc)) * (8 * 768);
        for (int i = 0; i < 2; i++) {
          mbar_wait(bars, B_GE + c.slot, c.phase ^ 1);
          mbar_expect_tx(bars + (B_GF + c.slot) * 8, XBYTES);
          bulk_g2s(sm + SM_G + c.slot * XBYTES, src + i * 3072, XBYTES, bars + (B_GF + c.slot) * 8);
          c.next();
        }
      };
      ldW(j < 2 ? &P.wqB : &P.wqA, 0, 2 * h);
      for (int i = 0; i < 8; i++) ldX(j < 2 ? &P.xB : &P.xA, qp_batch(j, i) * SQ, 0);
      for (int i = 0; i < QPAD; i++) {
        mbar_wait(bars, B_GE + c.slot, c.phase ^ 1);
        mbar_arrive(bars + (B_GF + c.slot) * 8);
        c.next();
      }
      {
        const int bA = 4 * j + (h & 3);
        mbar_wait(bars, B_RDY + 1, 0);
        Cursor<NGS> c0 = c;
        for (int i = 0; i < 3; i++) { mbar_wait(bars, B_GE + c.slot, c.phase ^ 1); c.next(); }
        mbar_expect_tx(bars + (B_GF + c0.slot) * 8, 32768);
        tma_3d(sm + SM_G + c0.slot * XBYTES, &P.qA, 0, (bA * NGRP + kc) * 192 + 64, 0, bars + (B_GF + c0.slot) * 8);
        tma_3d(sm + SM_G + c0.slot * XBYTES + 16384, &P.qA, 0, (bA * NGRP + kc) * 192 + 128, 0, bars + (B_GF + c0.slot) * 8);
        mbar_arrive(bars + (B_GF + c0.slot + 1) * 8);
        mbar_arrive(bars + (B_GF + c0.slot + 2) * 8);
      }
      ldW(&P.woA, kc * 512, 2 * n_t);
      for (int s = 0; s < 4; s++) {
        mbar_wait(bars, B_RDY + 5 + s, 0);
        ldX(&P.oA, (4 * j + s) * SQ, kc * 8);
      }
      ldW(&P.woB, kc * 512, 2 * n_t);
      for (int s = 0; s < 4; s++) {
        mbar_wait(bars, B_RDY + 9 + s, 0);
        ldX(&P.oB, (4 * j + s) * SQ, kc * 8);
        if (s == 0) { for (int q = 0; q < 4; q++) ldF(0, q); }
        else if (s == 1) ldF(1, 0);
        else if (s == 2) { ldF(1, 1); ldF(1, 2); }
        else ldF(1, 3);
      }
    } else if (warp == 2) {
      if (lane < 2) {
        const int nev = lane == 0 ? 16 : 5;
        int e = 0;
        while (e < nev) {
          if (mbar_test(bars + ((lane == 0 ? B_EVG : B_EVA) + e) * 8, 0)) {
            __threadfence();
            unsigned* f;
            if (lane == 0) {
              if (e < 8) {
                const int b = qp_batch(j, e);
                f = (j < 2) ? &g_flags.qb_flag[(b * NH + h) * 8] : &g_flags.qa_cnt[(b * NGRP + kc) * 8];
              } else {
                f = &g_flags.part_cnt[(((e < 12 ? 0 : 1) * NB + 4 * j + (e & 3)) * 4 + n_t) * 8];
              }
            } else {
              f = (e == 1) ? &g_flags.oa_cnt[((4 * j + (h & 3)) * NGRP + kc) * 8]
                           : &g_flags.ob_cnt[((4 * j + (e == 0 ? 0 : e - 1)) * NGRP + kc) * 8];
            }
            red_add(f, 1);
            e++;
          } else {
            if (expired(bars)) break;
            __nanosleep(200);
          }
        }
      }
    } else if (warp == 3) {
      if (lane < 21) {
        const unsigned* f;
        unsigned target;
        if (lane < 5) {
          if (lane == 1) { f = &g_flags.qa_cnt[((4 * j + (h & 3)) * NGRP + kc) * 8]; target = 4 * ep1; }
          else { f = &g_flags.qb_flag[((4 * j + (lane == 0 ? 0 : lane - 1)) * NH + h) * 8]; target = ep1; }
        } else if (lane < 9) { f = &g_flags.oa_cnt[((4 * j + lane - 5) * NGRP + kc) * 8]; target = ep1; }
        else if (lane < 13) { f = &g_flags.ob_cnt[((4 * j + lane - 9) * NGRP + kc) * 8]; target = 4 * ep1; }
        else { f = &g_flags.part_cnt[((((lane - 13) >> 2) * NB + 4 * j + ((lane - 13) & 3)) * 4 + n_t) * 8]; target = 8 * ep1; }
        bool done = false;
        while (true) {
          if (!done && (int)(ld_acquire(f) - target) >= 0) {
            fence_proxy_async_global();
            mbar_arrive(bars + (B_RDY + lane) * 8);
            done = true;
          }
          if (__all_sync(0x1fffffu, done)) break;
          if (__any_sync(0x1fffffu, expired(bars))) break;
          __nanosleep(200);
        }
      }
    }
  } else {
    asm volatile("setmaxnreg.inc.sync.aligned.u32 160;");
    if (wg == 0) {
      Cursor<NKVS> cur; cur.init(0);
      if (tid == 0) TSTAMP(1);
      attn_ss<false, true>(sm, bars, cur, 0, sm + SM_QS);
      signal_unit(bars, 0);
      if (tid == 0) TSTAMP(2);
      if (tid == 0) TSTAMP(3);
      attn_ss<true, true>(sm, bars, cur, 0, sm + SM_QS);
      signal_unit(bars, 1);
      if (tid == 0) TSTAMP(4);
#pragma unroll 1
      for (int u = 2; u < 5; u++) {
        if (tid == 0) TSTAMP(1 + 2 * u);
        attn_ss<false, true>(sm, bars, cur, u - 1, sm + SM_QS);
        signal_unit(bars, u);
        if (tid == 0) TSTAMP(2 + 2 * u);
      }
    } else {
      Cursor<NGS> gc; gc.init(0);
      gemm_qp(sm, bars, gc);
      {
        mbar_wait(bars, B_EVA + 0, 0);
        const bool leader = (tid & 31) == 0;
        for (int i = 0; i < QPAD; i++) {
          mbar_wait(bars, B_GF + gc.slot, gc.phase);
          if (leader) mbar_arrive(bars + (B_GE + gc.slot) * 8);
          gc.next();
        }
        const int q0 = gc.slot;
        for (int i = 0; i < 3; i++) { mbar_wait(bars, B_GF + gc.slot, gc.phase); gc.next(); }
        Cursor<NKVS> cur; cur.init(17);
        attn_ss<true, false>(sm, bars, cur, 0, sm + SM_G + q0 * XBYTES + (wg - 1) * 16384);
        if (leader) for (int i = 0; i < 3; i++) mbar_arrive(bars + (B_GE + q0 + i) * 8);
        signal_unit(bars, 1);
      }
      gemm_op(sm, bars, gc, P.out);
      if (tid == 128) TSTAMP(48);
    }
  }
}

typedef CUresult (*EncodeFn)(CUtensorMap*, CUtensorMapDataType, cuuint32_t, void*, const cuuint64_t*, const cuuint64_t*,
                             const cuuint32_t*, const cuuint32_t*, CUtensorMapInterleave, CUtensorMapSwizzle,
                             CUtensorMapL2promotion, CUtensorMapFloatOOBfill);

static bool make_map(EncodeFn fn, CUtensorMap* m, const void* base, uint64_t rows, uint64_t row_elems, uint32_t box_rows,
                     uint32_t box_depth = 2) {
  cuuint64_t dims[3] = {64, rows, row_elems / 64};
  cuuint64_t strides[2] = {row_elems * 2, 128};
  cuuint32_t box[3] = {64, box_rows, box_depth};
  cuuint32_t estr[3] = {1, 1, 1};
  CUresult r = fn(m, CU_TENSOR_MAP_DATA_TYPE_BFLOAT16, 3, const_cast<void*>(base), dims, strides, box, estr,
                  CU_TENSOR_MAP_INTERLEAVE_NONE, CU_TENSOR_MAP_SWIZZLE_128B, CU_TENSOR_MAP_L2_PROMOTION_L2_256B,
                  CU_TENSOR_MAP_FLOAT_OOB_FILL_NONE);
  if (r != CUDA_SUCCESS) fprintf(stderr, "cuTensorMapEncodeTiled failed: %d\n", (int)r);
  return r == CUDA_SUCCESS;
}

}

extern "C" void kernel_launch(void* const* d_in, const int* in_sizes, int n_in, void* d_out, int out_size) {
  using namespace mk;
  static Params P;
  static bool init = false;
  static void* cached[11] = {0};
  bool same = init;
  for (int i = 0; i < 10; i++) same = same && (cached[i] == d_in[i]);
  same = same && (cached[10] == d_out);
  if (!same) {
    void* fnp = nullptr;
    cudaDriverEntryPointQueryResult qr;
    cudaGetDriverEntryPoint("cuTensorMapEncodeTiled", &fnp, cudaEnableDefault, &qr);
    EncodeFn fn = (EncodeFn)fnp;
    void *qa, *qb, *oa, *ob;
    cudaGetSymbolAddress(&qa, g_QA); cudaGetSymbolAddress(&qb, g_QB);
    cudaGetSymbolAddress(&oa, g_OA); cudaGetSymbolAddress(&ob, g_OB);
    make_map(fn, &P.xA, d_in[0], 768, 512, 48);
    make_map(fn, &P.kA, d_in[1], (uint64_t)NB * NGRP * SK, 128, 64);
    make_map(fn, &P.vA, d_in[2], (uint64_t)NB * NGRP * SK, 128, 64);
    make_map(fn, &P.wqA, d_in[3], 512, 4096, 16);
    make_map(fn, &P.woA, d_in[4], 4096, 512, 16);
    make_map(fn, &P.xB, d_in[5], 768, 512, 48);
    make_map(fn, &P.kB, d_in[6], (uint64_t)NB * NH * SK, 128, 64);
    make_map(fn, &P.vB, d_in[7], (uint64_t)NB * NH * SK, 128, 64);
    make_map(fn, &P.wqB, d_in[8], 512, 4096, 16);
    make_map(fn, &P.woB, d_in[9], 4096, 512, 16);
    make_map(fn, &P.qA, qa, (uint64_t)NB * NGRP * 192, 128, 64);
    make_map(fn, &P.qB, qb, (uint64_t)NB * NH * SQ + 16, 128, 64);
    make_map(fn, &P.oA, oa, 768, 4096, 48);
    make_map(fn, &P.oB, ob, 768, 4096, 48);
    P.out = (bf16*)d_out;
    P.pkA = (const bf16*)d_in[1]; P.pvA = (const bf16*)d_in[2]; P.pwoA = (const bf16*)d_in[4];
    P.pkB = (const bf16*)d_in[6]; P.pvB = (const bf16*)d_in[7]; P.pwoB = (const bf16*)d_in[9];
    cudaFuncSetAttribute(fused_kernel, cudaFuncAttributeMaxDynamicSharedMemorySize, SM_TOTAL);
    for (int i = 0; i < 10; i++) cached[i] = d_in[i];
    cached[10] = d_out;
    init = true;
  }
  fused_kernel<<<NCTA, NTHREADS, SM_TOTAL>>>(P);
}
```

```cpp
#include <cuda_runtime.h>
#include <cuda_bf16.h>
#include <cuda.h>
#include <stdint.h>
#include <stdio.h>

namespace mk {

typedef __nv_bfloat16 bf16;

constexpr int NB = 16, SQ = 48, DM = 512, NH = 32, NGRP = 8, SK = 512, DH = 128;
constexpr int SLOT = 16384;
#define NKVS 8
#define NGS 5
#define KV_START_DELAY 0
#define POLL_NS 64
#define WAIT_HINT_NS 100000u
constexpr int XBYTES = 12288;
constexpr int WREG = 27;
constexpr int SM_QS = 0;
constexpr int SM_KV = 16384;
constexpr int SM_G = SM_KV + NKVS * SLOT;
constexpr int SM_WS = SM_G + NGS * XBYTES;
constexpr int SM_BAR = SM_WS + (32 - WREG) * 4096;
constexpr int SM_TOTAL = SM_BAR + 1024 + 1024;
constexpr int NEXT = (NKVS * SLOT) / XBYTES;
constexpr int NWIDE = NGS + NEXT;
constexpr int SM_EXT = SM_G - NEXT * XBYTES;
static_assert(NEXT >= WREG / 3, "the first weight tile is loaded into the extra slots");
constexpr int QP_ENTRIES = 8 * 4;
constexpr int QPAD = (QP_ENTRIES % NGS + 3 > NGS) ? NGS - QP_ENTRIES % NGS : 0;
constexpr int NCTA = 128;
constexpr int NTHREADS = 512;

constexpr int B_KVF = 0;
constexpr int B_KVE = B_KVF + NKVS;
constexpr int B_GF = B_KVE + NKVS;
constexpr int B_GE = B_GF + NGS;
constexpr int B_EVG = B_GE + NGS;
constexpr int B_EVA = B_EVG + 16;
constexpr int B_WSF = B_EVA + 5;
constexpr int B_WSE = B_WSF + 1;
constexpr int B_WQF = B_WSE + 1;
constexpr int B_WQE = B_WQF + WREG / 3;
constexpr int B_XF = B_WQE + 1;
constexpr int B_XE = B_XF + NWIDE;
constexpr int B_RDY = B_XE + NWIDE;
constexpr int B_END = B_RDY + 21;
static_assert(B_END * 8 + 16 <= 1024 && B_END <= 512, "barrier region");
static_assert(SM_TOTAL <= 232448, "smem");

struct alignas(64) Params {
  CUtensorMap kA, vA, kB, vB;
  CUtensorMap qA, qB;
  CUtensorMap xA, xB, oA, oB;
  CUtensorMap wqA, wqB, woA, woB;
  CUtensorMap wqAt, wqBt, woAt, woBt;
  bf16* out;
  const bf16 *pkA, *pvA, *pkB, *pvB, *pwoA, *pwoB;
};

__device__ bf16 g_QA[NB * NGRP * 192 * DH];
__device__ bf16 g_QB[NB * NH * SQ * DH + 16 * DH];
__device__ bf16 g_OA[NB * SQ * NH * DH];
__device__ bf16 g_OB[NB * SQ * NH * DH];
__device__ uint4 g_part[2 * NB * 4 * 8 * 8 * 96];
struct Flags {
  unsigned epoch;
  unsigned pad0[31];
  unsigned started;
  unsigned pad1[31];
  unsigned qa_cnt[NB * NGRP * 8];
  unsigned qb_flag[NB * NH * 8];
  unsigned oa_cnt[NB * NGRP * 8];
  unsigned ob_cnt[NB * NGRP * 8];
  unsigned part_cnt[2 * NB * 4 * 8];
};
__device__ Flags g_flags;

#define TSTAMP(idx) do {} while (0)

__device__ __forceinline__ uint32_t smem_u32(const void* p) { return (uint32_t)__cvta_generic_to_shared(p); }
__device__ __forceinline__ void mbar_init(uint32_t bar, uint32_t cnt) {
  asm volatile("mbarrier.init.shared::cta.b64 [%0], %1;" ::"r"(bar), "r"(cnt) : "memory");
}
__device__ __forceinline__ void mbar_expect_tx(uint32_t bar, uint32_t bytes) {
  asm volatile("mbarrier.arrive.expect_tx.shared::cta.b64 _, [%0], %1;" ::"r"(bar), "r"(bytes) : "memory");
}
__device__ __forceinline__ void mbar_arrive(uint32_t bar) {
  asm volatile("mbarrier.arrive.shared::cta.b64 _, [%0];" ::"r"(bar) : "memory");
}
__device__ __forceinline__ void mbar_arrive_n(uint32_t bar, uint32_t n) {
  asm volatile("mbarrier.arrive.shared::cta.b64 _, [%0], %1;" ::"r"(bar), "r"(n) : "memory");
}
__device__ __forceinline__ bool mbar_try(uint32_t bar, uint32_t parity) {
  uint32_t ok;
  asm volatile("{\n.reg .pred p;\nmbarrier.try_wait.parity.shared::cta.b64 p, [%1], %2, %3;\nselp.u32 %0, 1, 0, p;\n}"
               : "=r"(ok) : "r"(bar), "r"(parity), "r"(WAIT_HINT_NS) : "memory");
  return ok != 0;
}
__device__ __forceinline__ bool mbar_test(uint32_t bar, uint32_t parity) {
  uint32_t ok;
  asm volatile("{\n.reg .pred p;\nmbarrier.test_wait.parity.shared::cta.b64 p, [%1], %2;\nselp.u32 %0, 1, 0, p;\n}"
               : "=r"(ok) : "r"(bar), "r"(parity) : "memory");
  return ok != 0;
}
__device__ __forceinline__ bool expired(uint32_t bars) {
  uint32_t t0, t1;
  asm volatile("ld.volatile.shared.u32 %0, [%1];" : "=r"(t0) : "r"(bars + B_END * 8 + 8));
  asm volatile("mov.u32 %0, %%clock;" : "=r"(t1));
  return (t1 - t0) > 1900000000u;
}
__device__ __forceinline__ int opaque_tid() {
  int t;
  asm volatile("mov.u32 %0, %%tid.x;" : "=r"(t));
  return t;
}
__device__ __forceinline__ int opaque_cta() {
  int t;
  asm volatile("mov.u32 %0, %%ctaid.x;" : "=r"(t));
  return t;
}
__device__ __forceinline__ void mbar_wait(uint32_t bars, int idx, uint32_t parity) {
  while (!mbar_try(bars + idx * 8, parity)) {
    if (expired(bars)) break;
  }
}
__device__ __forceinline__ unsigned ld_acquire(const unsigned* p) {
  unsigned v;
  asm volatile("ld.acquire.gpu.global.u32 %0, [%1];" : "=r"(v) : "l"(p) : "memory");
  return v;
}
__device__ __forceinline__ void red_add(unsigned* p, unsigned v) {
  asm volatile("red.relaxed.gpu.global.add.u32 [%0], %1;" ::"l"(p), "r"(v) : "memory");
}
__device__ __forceinline__ void wait_flag(uint32_t bars, const unsigned* p, unsigned target) {
  while ((int)(ld_acquire(p) - target) < 0) {
    __nanosleep(64);
    if (expired(bars)) break;
  }
}
__device__ __forceinline__ void fence_proxy_async() { asm volatile("fence.proxy.async.shared::cta;" ::: "memory"); }
__device__ __forceinline__ void fence_proxy_async_global() { asm volatile("fence.proxy.async.global;" ::: "memory"); }
__device__ __forceinline__ void tma_3d(uint32_t dst, const CUtensorMap* map, int c0, int c1, int c2, uint32_t bar) {
  asm volatile(
      "cp.async.bulk.tensor.3d.shared::cluster.global.mbarrier::complete_tx::bytes [%0], [%1, {%3, %4, %5}], [%2];" ::"r"(dst),
      "l"(map), "r"(bar), "r"(c0), "r"(c1), "r"(c2)
      : "memory");
}
__device__ __forceinline__ void tma_3d_hint(uint32_t dst, const CUtensorMap* map, int c0, int c1, int c2, uint32_t bar, uint64_t pol) {
  asm volatile(
      "cp.async.bulk.tensor.3d.shared::cluster.global.mbarrier::complete_tx::bytes.L2::cache_hint [%0], [%1, {%3, %4, %5}], [%2], %6;" ::"r"(dst),
      "l"(map), "r"(bar), "r"(c0), "r"(c1), "r"(c2), "l"(pol)
      : "memory");
}
__device__ __forceinline__ uint64_t policy_evict_first() {
  uint64_t pol;
  asm volatile("createpolicy.fractional.L2::evict_first.b64 %0, 1.0;" : "=l"(pol));
  return pol;
}
__device__ __forceinline__ void bulk_g2s(uint32_t dst, const void* src, uint32_t bytes, uint32_t bar) {
  asm volatile("cp.async.bulk.shared::cluster.global.mbarrier::complete_tx::bytes [%0], [%1], %2, [%3];" ::"r"(dst), "l"(src),
               "r"(bytes), "r"(bar)
               : "memory");
}
__device__ __forceinline__ void touch_page(const void* p) {
  asm volatile("cp.async.bulk.prefetch.L2.global [%0], 16;" ::"l"(p) : "memory");
}
__device__ __forceinline__ void prefetch_tmap(const CUtensorMap* map) {
  asm volatile("prefetch.tensormap [%0];" ::"l"(map) : "memory");
}
__device__ __forceinline__ void ldsm_x4(uint32_t (&r)[4], uint32_t addr) {
  asm volatile("ldmatrix.sync.aligned.m8n8.x4.shared.b16 {%0,%1,%2,%3}, [%4];"
               : "=r"(r[0]), "=r"(r[1]), "=r"(r[2]), "=r"(r[3]) : "r"(addr) : "memory");
}
__device__ __forceinline__ void ldsm_x4_t(uint32_t (&r)[4], uint32_t addr) {
  asm volatile("ldmatrix.sync.aligned.m8n8.x4.trans.shared.b16 {%0,%1,%2,%3}, [%4];"
               : "=r"(r[0]), "=r"(r[1]), "=r"(r[2]), "=r"(r[3]) : "r"(addr) : "memory");
}
__device__ __forceinline__ void stsm_x4_t(uint32_t addr, uint32_t r0, uint32_t r1, uint32_t r2, uint32_t r3) {
  asm volatile("stmatrix.sync.aligned.m8n8.x4.trans.shared.b16 [%0], {%1,%2,%3,%4};" ::"r"(addr), "r"(r0), "r"(r1), "r"(r2),
               "r"(r3)
               : "memory");
}
__constant__ uint32_t c_zero;
__device__ __forceinline__ uint32_t dep_on(uint32_t addr, uint32_t loaded) { return addr + (loaded & c_zero); }
__device__ __forceinline__ void named_bar(int id, int n) { asm volatile("bar.sync %0, %1;" ::"r"(id), "r"(n) : "memory"); }
__device__ __forceinline__ void wg_fence() { asm volatile("wgmma.fence.sync.aligned;" ::: "memory"); }
__device__ __forceinline__ void wg_commit() { asm volatile("wgmma.commit_group.sync.aligned;" ::: "memory"); }
template <int N>
__device__ __forceinline__ void wg_wait() { asm volatile("wgmma.wait_group.sync.aligned %0;" ::"n"(N) : "memory"); }
template <int N>
__device__ __forceinline__ void fence_regs(float (&a)[N]) {
#pragma unroll
  for (int i = 0; i < N; i++) asm volatile("" : "+f"(a[i])::"memory");
}
__device__ __forceinline__ uint64_t make_desc(uint32_t addr, uint32_t lbo, uint32_t sbo) {
  return (uint64_t)((addr & 0x3FFFF) >> 4) | ((uint64_t)(lbo >> 4) << 16) | ((uint64_t)(sbo >> 4) << 32) | (1ull << 62);
}
__device__ __forceinline__ uint32_t pack_bf16(float lo, float hi) {
  uint32_t r;
  asm("cvt.rn.bf16x2.f32 %0, %1, %2;" : "=r"(r) : "f"(hi), "f"(lo));
  return r;
}
__device__ __forceinline__ float ex2(float x) {
  float y;
  asm("ex2.approx.ftz.f32 %0, %1;" : "=f"(y) : "f"(x));
  return y;
}

__device__ __forceinline__ float rcp(float x) {
  float y;
  asm("rcp.approx.ftz.f32 %0, %1;" : "=f"(y) : "f"(x));
  return y;
}

__device__ __forceinline__ void wgmma_n64(float (&d)[32], const uint32_t (&a)[4], uint64_t desc, int scale_d) {
  asm volatile(
      "{\n.reg .pred p;\nsetp.ne.b32 p, %37, 0;\n"
      "wgmma.mma_async.sync.aligned.m64n64k16.f32.bf16.bf16 "
      "{%0,%1,%2,%3,%4,%5,%6,%7,%8,%9,%10,%11,%12,%13,%14,%15,%16,%17,%18,%19,%20,%21,%22,%23,%24,%25,%26,%27,%28,%29,%30,%31},"
      "{%32,%33,%34,%35}, %36, p, 1, 1, 0;\n}"
      : "+f"(d[0]), "+f"(d[1]), "+f"(d[2]), "+f"(d[3]), "+f"(d[4]), "+f"(d[5]), "+f"(d[6]), "+f"(d[7]), "+f"(d[8]), "+f"(d[9]),
        "+f"(d[10]), "+f"(d[11]), "+f"(d[12]), "+f"(d[13]), "+f"(d[14]), "+f"(d[15]), "+f"(d[16]), "+f"(d[17]), "+f"(d[18]),
        "+f"(d[19]), "+f"(d[20]), "+f"(d[21]), "+f"(d[22]), "+f"(d[23]), "+f"(d[24]), "+f"(d[25]), "+f"(d[26]), "+f"(d[27]),
        "+f"(d[28]), "+f"(d[29]), "+f"(d[30]), "+f"(d[31])
      : "r"(a[0]), "r"(a[1]), "r"(a[2]), "r"(a[3]), "l"(desc), "r"(scale_d));
}
__device__ __forceinline__ void wgmma_n64_ss(float (&d)[32], uint64_t da, uint64_t db, int scale_d) {
  asm volatile(
      "{\n.reg .pred p;\nsetp.ne.b32 p, %34, 0;\n"
      "wgmma.mma_async.sync.aligned.m64n64k16.f32.bf16.bf16 "
      "{%0,%1,%2,%3,%4,%5,%6,%7,%8,%9,%10,%11,%12,%13,%14,%15,%16,%17,%18,%19,%20,%21,%22,%23,%24,%25,%26,%27,%28,%29,%30,%31},"
      "%32, %33, p, 1, 1, 0, 0;\n}"
      : "+f"(d[0]), "+f"(d[1]), "+f"(d[2]), "+f"(d[3]), "+f"(d[4]), "+f"(d[5]), "+f"(d[6]), "+f"(d[7]), "+f"(d[8]), "+f"(d[9]),
        "+f"(d[10]), "+f"(d[11]), "+f"(d[12]), "+f"(d[13]), "+f"(d[14]), "+f"(d[15]), "+f"(d[16]), "+f"(d[17]), "+f"(d[18]),
        "+f"(d[19]), "+f"(d[20]), "+f"(d[21]), "+f"(d[22]), "+f"(d[23]), "+f"(d[24]), "+f"(d[25]), "+f"(d[26]), "+f"(d[27]),
        "+f"(d[28]), "+f"(d[29]), "+f"(d[30]), "+f"(d[31])
      : "l"(da), "l"(db), "r"(scale_d));
}
__device__ __forceinline__ void wgmma_n64_t(float (&d)[32], const uint32_t (&a)[4], uint64_t desc, int scale_d) {
  asm volatile(
      "{\n.reg .pred p;\nsetp.ne.b32 p, %37, 0;\n"
      "wgmma.mma_async.sync.aligned.m64n64k16.f32.bf16.bf16 "
      "{%0,%1,%2,%3,%4,%5,%6,%7,%8,%9,%10,%11,%12,%13,%14,%15,%16,%17,%18,%19,%20,%21,%22,%23,%24,%25,%26,%27,%28,%29,%30,%31},"
      "{%32,%33,%34,%35}, %36, p, 1, 1, 1;\n}"
      : "+f"(d[0]), "+f"(d[1]), "+f"(d[2]), "+f"(d[3]), "+f"(d[4]), "+f"(d[5]), "+f"(d[6]), "+f"(d[7]), "+f"(d[8]), "+f"(d[9]),
        "+f"(d[10]), "+f"(d[11]), "+f"(d[12]), "+f"(d[13]), "+f"(d[14]), "+f"(d[15]), "+f"(d[16]), "+f"(d[17]), "+f"(d[18]),
        "+f"(d[19]), "+f"(d[20]), "+f"(d[21]), "+f"(d[22]), "+f"(d[23]), "+f"(d[24]), "+f"(d[25]), "+f"(d[26]), "+f"(d[27]),
        "+f"(d[28]), "+f"(d[29]), "+f"(d[30]), "+f"(d[31])
      : "r"(a[0]), "r"(a[1]), "r"(a[2]), "r"(a[3]), "l"(desc), "r"(scale_d));
}
__device__ __forceinline__ void wgmma_n32_ss(float (&d)[16], uint64_t da, uint64_t db, int scale_d) {
  asm volatile(
      "{\n.reg .pred p;\nsetp.ne.b32 p, %18, 0;\n"
      "wgmma.mma_async.sync.aligned.m64n32k16.f32.bf16.bf16 "
      "{%0,%1,%2,%3,%4,%5,%6,%7,%8,%9,%10,%11,%12,%13,%14,%15},"
      "%16, %17, p, 1, 1, 0, 0;\n}"
      : "+f"(d[0]), "+f"(d[1]), "+f"(d[2]), "+f"(d[3]), "+f"(d[4]), "+f"(d[5]), "+f"(d[6]), "+f"(d[7]), "+f"(d[8]), "+f"(d[9]),
        "+f"(d[10]), "+f"(d[11]), "+f"(d[12]), "+f"(d[13]), "+f"(d[14]), "+f"(d[15])
      : "l"(da), "l"(db), "r"(scale_d));
}
__device__ __forceinline__ void wgmma_n32(float (&d)[16], const uint32_t (&a)[4], uint64_t desc, int scale_d) {
  asm volatile(
      "{\n.reg .pred p;\nsetp.ne.b32 p, %21, 0;\n"
      "wgmma.mma_async.sync.aligned.m64n32k16.f32.bf16.bf16 "
      "{%0,%1,%2,%3,%4,%5,%6,%7,%8,%9,%10,%11,%12,%13,%14,%15},"
      "{%16,%17,%18,%19}, %20, p, 1, 1, 0;\n}"
      : "+f"(d[0]), "+f"(d[1]), "+f"(d[2]), "+f"(d[3]), "+f"(d[4]), "+f"(d[5]), "+f"(d[6]), "+f"(d[7]), "+f"(d[8]), "+f"(d[9]),
        "+f"(d[10]), "+f"(d[11]), "+f"(d[12]), "+f"(d[13]), "+f"(d[14]), "+f"(d[15])
      : "r"(a[0]), "r"(a[1]), "r"(a[2]), "r"(a[3]), "l"(desc), "r"(scale_d));
}
__device__ __forceinline__ void wgmma_n128_t(float (&d)[64], const uint32_t (&a)[4], uint64_t desc, int scale_d) {
  asm volatile(
      "{\n.reg .pred p;\nsetp.ne.b32 p, %69, 0;\n"
      "wgmma.mma_async.sync.aligned.m64n128k16.f32.bf16.bf16 "
      "{%0,%1,%2,%3,%4,%5,%6,%7,%8,%9,%10,%11,%12,%13,%14,%15,%16,%17,%18,%19,%20,%21,%22,%23,%24,%25,%26,%27,%28,%29,%30,%31,"
      "%32,%33,%34,%35,%36,%37,%38,%39,%40,%41,%42,%43,%44,%45,%46,%47,%48,%49,%50,%51,%52,%53,%54,%55,%56,%57,%58,%59,%60,%61,%62,%63},"
      "{%64,%65,%66,%67}, %68, p, 1, 1, 1;\n}"
      : "+f"(d[0]), "+f"(d[1]), "+f"(d[2]), "+f"(d[3]), "+f"(d[4]), "+f"(d[5]), "+f"(d[6]), "+f"(d[7]), "+f"(d[8]), "+f"(d[9]),
        "+f"(d[10]), "+f"(d[11]), "+f"(d[12]), "+f"(d[13]), "+f"(d[14]), "+f"(d[15]), "+f"(d[16]), "+f"(d[17]), "+f"(d[18]),
        "+f"(d[19]), "+f"(d[20]), "+f"(d[21]), "+f"(d[22]), "+f"(d[23]), "+f"(d[24]), "+f"(d[25]), "+f"(d[26]), "+f"(d[27]),
        "+f"(d[28]), "+f"(d[29]), "+f"(d[30]), "+f"(d[31]), "+f"(d[32]), "+f"(d[33]), "+f"(d[34]), "+f"(d[35]), "+f"(d[36]),
        "+f"(d[37]), "+f"(d[38]), "+f"(d[39]), "+f"(d[40]), "+f"(d[41]), "+f"(d[42]), "+f"(d[43]), "+f"(d[44]), "+f"(d[45]),
        "+f"(d[46]), "+f"(d[47]), "+f"(d[48]), "+f"(d[49]), "+f"(d[50]), "+f"(d[51]), "+f"(d[52]), "+f"(d[53]), "+f"(d[54]),
        "+f"(d[55]), "+f"(d[56]), "+f"(d[57]), "+f"(d[58]), "+f"(d[59]), "+f"(d[60]), "+f"(d[61]), "+f"(d[62]), "+f"(d[63])
      : "r"(a[0]), "r"(a[1]), "r"(a[2]), "r"(a[3]), "l"(desc), "r"(scale_d));
}
__device__ __forceinline__ void wgmma_n48(float (&d)[24], const uint32_t (&a)[4], uint64_t desc, int scale_d) {
  asm volatile(
      "{\n.reg .pred p;\nsetp.ne.b32 p, %29, 0;\n"
      "wgmma.mma_async.sync.aligned.m64n48k16.f32.bf16.bf16 "
      "{%0,%1,%2,%3,%4,%5,%6,%7,%8,%9,%10,%11,%12,%13,%14,%15,%16,%17,%18,%19,%20,%21,%22,%23},"
      "{%24,%25,%26,%27}, %28, p, 1, 1, 0;\n}"
      : "+f"(d[0]), "+f"(d[1]), "+f"(d[2]), "+f"(d[3]), "+f"(d[4]), "+f"(d[5]), "+f"(d[6]), "+f"(d[7]), "+f"(d[8]), "+f"(d[9]),
        "+f"(d[10]), "+f"(d[11]), "+f"(d[12]), "+f"(d[13]), "+f"(d[14]), "+f"(d[15]), "+f"(d[16]), "+f"(d[17]), "+f"(d[18]),
        "+f"(d[19]), "+f"(d[20]), "+f"(d[21]), "+f"(d[22]), "+f"(d[23])
      : "r"(a[0]), "r"(a[1]), "r"(a[2]), "r"(a[3]), "l"(desc), "r"(scale_d));
}

__device__ __forceinline__ void wgmma_n48_ss(float (&d)[24], uint64_t descA, uint64_t descB) {
  asm volatile(
      "{\n.reg .pred p;\nsetp.ne.b32 p, 1, 0;\n"
      "wgmma.mma_async.sync.aligned.m64n48k16.f32.bf16.bf16 "
      "{%0,%1,%2,%3,%4,%5,%6,%7,%8,%9,%10,%11,%12,%13,%14,%15,%16,%17,%18,%19,%20,%21,%22,%23},"
      "%24, %25, p, 1, 1, 1, 0;\n}"
      : "+f"(d[0]), "+f"(d[1]), "+f"(d[2]), "+f"(d[3]), "+f"(d[4]), "+f"(d[5]), "+f"(d[6]), "+f"(d[7]), "+f"(d[8]), "+f"(d[9]),
        "+f"(d[10]), "+f"(d[11]), "+f"(d[12]), "+f"(d[13]), "+f"(d[14]), "+f"(d[15]), "+f"(d[16]), "+f"(d[17]), "+f"(d[18]),
        "+f"(d[19]), "+f"(d[20]), "+f"(d[21]), "+f"(d[22]), "+f"(d[23])
      : "l"(descA), "l"(descB));
}
__device__ __forceinline__ uint32_t movmatrix_t(uint32_t x) {
  uint32_t y;
  asm volatile("movmatrix.sync.aligned.m8n8.trans.b16 %0, %1;" : "=r"(y) : "r"(x));
  return y;
}

template <int N>
struct Cursor {
  int slot;
  uint32_t phase;
  __device__ __forceinline__ void init(int count) { slot = count % N; phase = (count / N) & 1; }
  __device__ __forceinline__ void next() { if (++slot == N) { slot = 0; phase ^= 1; } }
};

template <int MODE>
struct GCur {
  int slot;
  uint32_t phase;
  __device__ __forceinline__ void init(int count) {
    constexpr int N = MODE == 0 ? NGS : (MODE == 1 ? NWIDE : WREG / 3);
    slot = count % N; phase = (count / N) & 1;
  }
  __device__ __forceinline__ void next() {
    constexpr int N = MODE == 0 ? NGS : (MODE == 1 ? NWIDE : WREG / 3);
    if (++slot == N) { slot = 0; phase ^= 1; }
  }
  __device__ __forceinline__ uint32_t off() const {
    if (MODE == 0) return SM_G + slot * XBYTES;
    if (MODE == 1) return SM_EXT + (slot < NGS ? slot + NEXT : slot - NGS) * XBYTES;
    return SM_EXT + slot * XBYTES;
  }
  __device__ __forceinline__ int full() const { return (MODE == 0 ? B_GF : (MODE == 1 ? B_XF : B_WQF)) + slot; }
  __device__ __forceinline__ int empty() const { return MODE == 2 ? B_WQE : (MODE == 0 ? B_GE : B_XE) + slot; }
};

constexpr float SM_C = 0.08838834764831845f * 1.4426950408889634f;
constexpr float RESCALE_T = 8.0f;

template <int NS>
__device__ __forceinline__ void softmax_step(const float (&s)[NS], uint32_t (&pf)[NS / 8][4], float (&o)[64],
                                             float& m0, float& m1, float& l0, float& l1, bool first) {
  float mx0 = fmaxf(s[0], s[1]), mx1 = fmaxf(s[2], s[3]);
#pragma unroll
  for (int j = 1; j < NS / 4; j++) {
    mx0 = fmaxf(mx0, fmaxf(s[4 * j], s[4 * j + 1]));
    mx1 = fmaxf(mx1, fmaxf(s[4 * j + 2], s[4 * j + 3]));
  }
  mx0 = fmaxf(mx0, __shfl_xor_sync(0xffffffffu, mx0, 1));
  mx1 = fmaxf(mx1, __shfl_xor_sync(0xffffffffu, mx1, 1));
  mx0 = fmaxf(mx0, __shfl_xor_sync(0xffffffffu, mx0, 2));
  mx1 = fmaxf(mx1, __shfl_xor_sync(0xffffffffu, mx1, 2));
  const bool grow = !((mx0 - m0) * SM_C <= RESCALE_T) || !((mx1 - m1) * SM_C <= RESCALE_T);
  if (__any_sync(0xffffffffu, grow)) {
    const float mn0 = fmaxf(m0, mx0), mn1 = fmaxf(m1, mx1);
    const float a0 = ex2((m0 - mn0) * SM_C), a1 = ex2((m1 - mn1) * SM_C);
    m0 = mn0; m1 = mn1;
    l0 *= a0; l1 *= a1;
    if (!first) {
#pragma unroll
      for (int j = 0; j < 16; j++) {
        o[4 * j] *= a0; o[4 * j + 1] *= a0; o[4 * j + 2] *= a1; o[4 * j + 3] *= a1;
      }
    }
  }
  const float mc0 = m0 * SM_C, mc1 = m1 * SM_C;
#pragma unroll
  for (int j = 0; j < NS / 4; j++) {
    const float p0 = ex2(fmaf(s[4 * j], SM_C, -mc0)), p1 = ex2(fmaf(s[4 * j + 1], SM_C, -mc0));
    const float p2 = ex2(fmaf(s[4 * j + 2], SM_C, -mc1)), p3 = ex2(fmaf(s[4 * j + 3], SM_C, -mc1));
    l0 += p0 + p1; l1 += p2 + p3;
    pf[j >> 1][(j & 1) * 2 + 0] = pack_bf16(p0, p1);
    pf[j >> 1][(j & 1) * 2 + 1] = pack_bf16(p2, p3);
  }
}

__device__ __forceinline__ bool sm_max(const float (&s)[16], float m0, float m1, float& mx0, float& mx1) {
  mx0 = fmaxf(fmaxf(fmaxf(s[0], s[1]), fmaxf(s[4], s[5])), fmaxf(fmaxf(s[8], s[9]), fmaxf(s[12], s[13])));
  mx1 = fmaxf(fmaxf(fmaxf(s[2], s[3]), fmaxf(s[6], s[7])), fmaxf(fmaxf(s[10], s[11]), fmaxf(s[14], s[15])));
  mx0 = fmaxf(mx0, __shfl_xor_sync(0xffffffffu, mx0, 1));
  mx1 = fmaxf(mx1, __shfl_xor_sync(0xffffffffu, mx1, 1));
  mx0 = fmaxf(mx0, __shfl_xor_sync(0xffffffffu, mx0, 2));
  mx1 = fmaxf(mx1, __shfl_xor_sync(0xffffffffu, mx1, 2));
  const bool grow = !((mx0 - m0) * SM_C <= RESCALE_T) || !((mx1 - m1) * SM_C <= RESCALE_T);
  return __any_sync(0xffffffffu, grow);
}
__device__ __forceinline__ void sm_exp(const float (&s)[16], uint32_t (&pf)[2][4], float (&o)[64], bool grow, float mx0, float mx1,
                                       float& m0, float& m1, float& l0, float& l1, bool first) {
  if (grow) {
    const float mn0 = fmaxf(m0, mx0), mn1 = fmaxf(m1, mx1);
    const float a0 = ex2((m0 - mn0) * SM_C), a1 = ex2((m1 - mn1) * SM_C);
    m0 = mn0; m1 = mn1;
    l0 *= a0; l1 *= a1;
    if (!first) {
#pragma unroll
      for (int j = 0; j < 16; j++) {
        o[4 * j] *= a0; o[4 * j + 1] *= a0; o[4 * j + 2] *= a1; o[4 * j + 3] *= a1;
      }
    }
  }
  const float mc0 = m0 * SM_C, mc1 = m1 * SM_C;
#pragma unroll
  for (int j = 0; j < 4; j++) {
    const float p0 = ex2(fmaf(s[4 * j], SM_C, -mc0)), p1 = ex2(fmaf(s[4 * j + 1], SM_C, -mc0));
    const float p2 = ex2(fmaf(s[4 * j + 2], SM_C, -mc1)), p3 = ex2(fmaf(s[4 * j + 3], SM_C, -mc1));
    l0 += p0 + p1; l1 += p2 + p3;
    pf[j >> 1][(j & 1) * 2 + 0] = pack_bf16(p0, p1);
    pf[j >> 1][(j & 1) * 2 + 1] = pack_bf16(p2, p3);
  }
}

template <bool isA>
__device__ __forceinline__ void attn_epilogue(const float (&o)[64], float l0, float l1, int slotB) {
  l0 += __shfl_xor_sync(0xffffffffu, l0, 1); l1 += __shfl_xor_sync(0xffffffffu, l1, 1);
  l0 += __shfl_xor_sync(0xffffffffu, l0, 2); l1 += __shfl_xor_sync(0xffffffffu, l1, 2);
  const float i0 = rcp(l0), i1 = rcp(l1);
  const int tid = opaque_tid(), cta = opaque_cta();
  const int h = cta >> 2, jg = cta & 3;
  const int r0 = (tid >> 5) * 16 + ((tid & 31) >> 2), r1 = r0 + 8;
  bf16 *orow0, *orow1;
  if (isA) {
    const int bA = 4 * jg + (h & 3);
    orow0 = g_OA + (size_t)(bA * SQ + r0 % SQ) * 4096 + ((h >> 2) * 4 + r0 / SQ) * DH;
    orow1 = g_OA + (size_t)(bA * SQ + r1 % SQ) * 4096 + ((h >> 2) * 4 + r1 / SQ) * DH;
  } else {
    orow0 = g_OB + (size_t)((4 * jg + slotB) * SQ + r0) * 4096 + h * DH;
    orow1 = orow0 + 8 * 4096;
  }
  const int q = tid & 3;
#pragma unroll
  for (int half = 0; half < 2; half++) {
    const float inv = half ? i1 : i0;
    bf16* orow = half ? orow1 : orow0;
#pragma unroll
    for (int g = 0; g < 4; g++) {
      uint32_t v[4];
#pragma unroll
      for (int k = 0; k < 4; k++) v[k] = pack_bf16(o[4 * (4 * g + k) + 2 * half] * inv, o[4 * (4 * g + k) + 2 * half + 1] * inv);
      {
        const bool odd = q & 1;
        const uint32_t s0 = odd ? v[0] : v[1], s1 = odd ? v[2] : v[3];
        const uint32_t r0_ = __shfl_xor_sync(0xffffffffu, s0, 1), r1_ = __shfl_xor_sync(0xffffffffu, s1, 1);
        if (odd) { v[0] = r0_; v[2] = r1_; } else { v[1] = r0_; v[3] = r1_; }
      }
      {
        const bool hi = q & 2;
        const uint32_t s0 = hi ? v[0] : v[2], s1 = hi ? v[1] : v[3];
        const uint32_t r0_ = __shfl_xor_sync(0xffffffffu, s0, 2), r1_ = __shfl_xor_sync(0xffffffffu, s1, 2);
        if (hi) { v[0] = r0_; v[1] = r1_; } else { v[2] = r0_; v[3] = r1_; }
      }
      *reinterpret_cast<uint4*>(orow + (4 * g + q) * 8) = make_uint4(v[0], v[1], v[2], v[3]);
    }
  }
}

template <bool isA, bool isWG0>
__device__ __forceinline__ void attn_ss(uint32_t sm, uint32_t bars, Cursor<NKVS>& cur, int slotB, uint32_t qs) {
  const int tid_ = opaque_tid();
  const bool leader = (tid_ & 31) == 0;
  constexpr uint32_t narr = isA ? 1 : 3;
  const bool active = isA || (tid_ >> 5) < 3;
  if (isWG0) {
    mbar_wait(bars, B_KVF + cur.slot, cur.phase);
    const uint32_t src = sm + SM_KV + cur.slot * SLOT + tid_ * 16, dst = qs + tid_ * 16;
    uint32_t x = 0;
#pragma unroll
    for (int i = 0; i < 8; i++) {
      uint4 v;
      asm volatile("ld.shared.v4.u32 {%0,%1,%2,%3}, [%4];" : "=r"(v.x), "=r"(v.y), "=r"(v.z), "=r"(v.w) : "r"(src + i * 2048) : "memory");
      asm volatile("st.shared.v4.u32 [%0], {%1,%2,%3,%4};" ::"r"(dst + i * 2048), "r"(v.x), "r"(v.y), "r"(v.z), "r"(v.w) : "memory");
      x ^= v.x;
    }
    const uint32_t rel = dep_on(bars + (B_KVE + cur.slot) * 8, x);
    __syncwarp();
    if (leader) mbar_arrive_n(rel, narr);
    cur.next();
    fence_proxy_async();
    named_bar(1, 128);
  } else {
    mbar_wait(bars, B_KVF + cur.slot, cur.phase);
    if (leader) mbar_arrive(bars + (B_KVE + cur.slot) * 8);
    cur.next();
  }
  float o[64];
  float s[32];
  float m0 = -INFINITY, m1 = -INFINITY, l0 = 0.f, l1 = 0.f;
  mbar_wait(bars, B_KVF + cur.slot, cur.phase);
  wg_fence();
#pragma unroll
  for (int ks = 0; ks < 8; ks++)
    wgmma_n64_ss(s, make_desc(qs + (ks >> 2) * 8192 + (ks & 3) * 32, 16, 1024),
                 make_desc(sm + SM_KV + cur.slot * SLOT + (ks >> 2) * 8192 + (ks & 3) * 32, 16, 1024), ks > 0);
  wg_commit();
  wg_wait<0>();
  fence_regs(s);
  if (leader) mbar_arrive_n(bars + (B_KVE + cur.slot) * 8, narr);
  cur.next();
#pragma unroll 1
  for (int t = 0; t < 8; t++) {
    uint32_t pf[4][4];
    if (active) softmax_step<32>(s, pf, o, m0, m1, l0, l1, t == 0);
    else {
#pragma unroll
      for (int k = 0; k < 4; k++) { pf[k][0] = 0; pf[k][1] = 0; pf[k][2] = 0; pf[k][3] = 0; }
    }
    const int vs = cur.slot; const uint32_t vp = cur.phase; cur.next();
    mbar_wait(bars, B_KVF + vs, vp);
    wg_fence();
#pragma unroll
    for (int kk = 0; kk < 4; kk++)
      wgmma_n128_t(o, pf[kk], make_desc(sm + SM_KV + vs * SLOT + kk * 2048, 8192, 1024), (t > 0) || (kk > 0));
    wg_commit();
    if (t < 7) {
      const int ks_ = cur.slot;
      mbar_wait(bars, B_KVF + ks_, cur.phase);
      cur.next();
      wg_fence();
#pragma unroll
      for (int ks = 0; ks < 8; ks++)
        wgmma_n64_ss(s, make_desc(qs + (ks >> 2) * 8192 + (ks & 3) * 32, 16, 1024),
                     make_desc(sm + SM_KV + ks_ * SLOT + (ks >> 2) * 8192 + (ks & 3) * 32, 16, 1024), ks > 0);
      wg_commit();
      wg_wait<1>();
      if (leader) mbar_arrive_n(bars + (B_KVE + vs) * 8, narr);
      wg_wait<0>();
      if (leader) mbar_arrive_n(bars + (B_KVE + ks_) * 8, narr);
    } else {
      wg_wait<0>();
      if (leader) mbar_arrive_n(bars + (B_KVE + vs) * 8, narr);
    }
    fence_regs(s); fence_regs(o);
  }
  if (active) attn_epilogue<isA>(o, l0, l1, slotB);
}

__device__ __forceinline__ void attn_b(uint32_t sm, uint32_t bars, Cursor<NKVS>& cur, int slotB) {
  const int tid_ = opaque_tid();
  const bool leader = (tid_ & 31) == 0;
  const bool active = (tid_ >> 5) < 3;
  const uint32_t qs = sm + SM_QS;
  {
    mbar_wait(bars, B_KVF + cur.slot, cur.phase);
    const uint32_t src = sm + SM_KV + cur.slot * SLOT + tid_ * 16, dst = qs + tid_ * 16;
    uint32_t x = 0;
#pragma unroll
    for (int i = 0; i < 8; i++) {
      uint4 v;
      asm volatile("ld.shared.v4.u32 {%0,%1,%2,%3}, [%4];" : "=r"(v.x), "=r"(v.y), "=r"(v.z), "=r"(v.w) : "r"(src + i * 2048) : "memory");
      asm volatile("st.shared.v4.u32 [%0], {%1,%2,%3,%4};" ::"r"(dst + i * 2048), "r"(v.x), "r"(v.y), "r"(v.z), "r"(v.w) : "memory");
      x ^= v.x;
    }
    const uint32_t rel = dep_on(bars + (B_KVE + cur.slot) * 8, x);
    __syncwarp();
    if (leader) mbar_arrive_n(rel, 3);
    cur.next();
    fence_proxy_async();
    named_bar(1, 128);
  }
  float o[64], sA[16], sB[16];
  uint32_t pf[2][4];
  float m0 = -INFINITY, m1 = -INFINITY, l0 = 0.f, l1 = 0.f, mx0 = 0.f, mx1 = 0.f;
#pragma unroll
  for (int k = 0; k < 2; k++) { pf[k][0] = 0; pf[k][1] = 0; pf[k][2] = 0; pf[k][3] = 0; }
  auto qk = [&](float (&d)[16], uint32_t kaddr) {
    wg_fence();
#pragma unroll
    for (int ks = 0; ks < 8; ks++)
      wgmma_n32_ss(d, make_desc(qs + (ks >> 2) * 8192 + (ks & 3) * 32, 16, 1024),
                   make_desc(kaddr + (ks >> 2) * 8192 + (ks & 3) * 32, 16, 1024), ks > 0);
    wg_commit();
  };
  auto pv = [&](uint32_t vaddr, int acc) {
    wg_fence();
#pragma unroll
    for (int kk = 0; kk < 2; kk++) wgmma_n128_t(o, pf[kk], make_desc(vaddr + kk * 2048, 8192, 1024), acc || (kk > 0));
    wg_commit();
  };
  int kslot = cur.slot;
  mbar_wait(bars, B_KVF + kslot, cur.phase);
  cur.next();
  qk(sA, sm + SM_KV + kslot * SLOT);
  wg_wait<0>();
  fence_regs(sA);
#pragma unroll 1
  for (int t = 0; t < 8; t++) {
    const int vslot = cur.slot; const uint32_t vph = cur.phase; cur.next();
    qk(sB, sm + SM_KV + kslot * SLOT + 4096);
    bool grow = false;
    if (active) {
      grow = sm_max(sA, m0, m1, mx0, mx1);
      sm_exp(sA, pf, o, grow, mx0, mx1, m0, m1, l0, l1, t == 0);
    }
    mbar_wait(bars, B_KVF + vslot, vph);
    pv(sm + SM_KV + vslot * SLOT, t > 0);
    wg_wait<1>();
    fence_regs(sB);
    if (leader) mbar_arrive_n(bars + (B_KVE + kslot) * 8, 3);
    if (t < 7) {
      kslot = cur.slot;
      mbar_wait(bars, B_KVF + kslot, cur.phase);
      cur.next();
    } else {
      kslot = vslot;
    }
    qk(sA, sm + SM_KV + kslot * SLOT);
    if (active) grow = sm_max(sB, m0, m1, mx0, mx1);
    wg_wait<1>();
    fence_regs(o);
    if (active) sm_exp(sB, pf, o, grow, mx0, mx1, m0, m1, l0, l1, false);
    pv(sm + SM_KV + vslot * SLOT + 4096, 1);
    wg_wait<0>();
    fence_regs(sA); fence_regs(o);
    if (leader) mbar_arrive_n(bars + (B_KVE + vslot) * 8, 3);
  }
  if (active) attn_epilogue<false>(o, l0, l1, slotB);
}

__device__ __forceinline__ void signal_unit(uint32_t bars, int u) {
  __syncwarp();
  if ((opaque_tid() & 31) == 0) mbar_arrive(bars + (B_EVA + u) * 8);
}

template <int MODE>
__device__ __forceinline__ void load_w(uint32_t (&wf)[WREG][4], uint32_t sm, uint32_t bars, GCur<MODE>& cur) {
  const int tid = opaque_tid();
  const int lane = tid & 31, warp = (tid >> 5) & 3, half = (tid >> 7) - 1;
  const int mi = lane >> 3, rr = lane & 7;
  const int chunk = warp * 2 + (mi & 1);
  const uint32_t off = sm + half * 6144 + ((mi >> 1) * 8 + rr) * 128 + ((chunk ^ rr) << 4);
  uint32_t all = 0;
#pragma unroll
  for (int c = 0; c < WREG / 3; c++) {
    mbar_wait(bars, cur.full(), cur.phase);
    const uint32_t base = off + cur.off();
#pragma unroll
    for (int ks = 0; ks < 3; ks++) ldsm_x4_t(wf[c * 3 + ks], base + ks * 2048);
    const uint32_t x = wf[c * 3][0] ^ wf[c * 3 + 1][0] ^ wf[c * 3 + 2][0];
    if (MODE == 2) {
      all ^= x;
    } else {
      const uint32_t rel = dep_on(bars + cur.empty() * 8, x);
      __syncwarp();
      if (lane == 0) mbar_arrive(rel);
    }
    cur.next();
  }
  if (MODE == 2) {
    const uint32_t rel = dep_on(bars + B_WQE * 8, all);
    __syncwarp();
    if (lane == 0) mbar_arrive(rel);
  }
}

template <int MODE>
__device__ __forceinline__ void brick(float (&acc)[24], const uint32_t (&wf)[WREG][4], uint32_t sm, uint32_t bars, GCur<MODE>& cur) {
  int prev_empty = 0;
  const int tid = opaque_tid();
  const bool leader = (tid & 31) == 0;
  const uint32_t ws = sm + SM_WS + ((tid >> 7) - 1) * ((32 - WREG) * 2048);
#pragma unroll
  for (int i = 0; i < 4; i++) {
    mbar_wait(bars, cur.full(), cur.phase);
    const uint32_t base = sm + cur.off();
    wg_fence();
#pragma unroll
    for (int ks = 0; ks < 8; ks++) {
      const uint64_t db = make_desc(base + (ks >> 2) * 6144 + (ks & 3) * 32, 16, 1024);
      if (i * 8 + ks < WREG) wgmma_n48(acc, wf[i * 8 + ks], db, (i > 0) || (ks > 0));
      else wgmma_n48_ss(acc, make_desc(ws + (i * 8 + ks - WREG) * 2048, 8192, 1024), db);
    }
    wg_commit();
    if (i > 0) {
      wg_wait<1>();
      if (leader) mbar_arrive(bars + prev_empty * 8);
    }
    prev_empty = cur.empty();
    cur.next();
  }
  wg_wait<0>();
  fence_regs(acc);
  if (leader) mbar_arrive(bars + prev_empty * 8);
}

__device__ __forceinline__ int qp_batch(int j, int i) { return 8 * (j & 1) + (i >> 1) + 4 * (i & 1); }
__device__ __forceinline__ void epi_q(const float (&acc)[24], int i) {
  const int tid = opaque_tid(), cta = opaque_cta();
  const int lane = tid & 31, w8 = (tid >> 5) - 4;
  const int h = cta >> 2, j = cta & 3, b = qp_batch(j, i);
  bf16* dst = (j < 2) ? g_QB + (size_t)((b * NH + h) * SQ) * DH : g_QA + (size_t)((b * NGRP + (h >> 2)) * 192 + (h & 3) * SQ) * DH;
  bf16* p = dst + w8 * 16 + (lane >> 2) * 128 + (lane & 3) * 2;
#pragma unroll
  for (int jb = 0; jb < 6; jb++) {
    const uint32_t lo = movmatrix_t(pack_bf16(acc[4 * jb + 0], acc[4 * jb + 1]));
    const uint32_t hi = movmatrix_t(pack_bf16(acc[4 * jb + 2], acc[4 * jb + 3]));
    *reinterpret_cast<uint32_t*>(p + jb * 8 * 128) = lo;
    *reinterpret_cast<uint32_t*>(p + jb * 8 * 128 + 8) = hi;
  }
}
__device__ __forceinline__ void epi_part(const float (&acc)[24], int br, int s) {
  const int tid = opaque_tid(), cta = opaque_cta();
  const int lane = tid & 31, w8 = (tid >> 5) - 4;
  const int h = cta >> 2, b = 4 * (cta & 3) + s;
  uint4* dst = g_part + ((size_t)(((br * NB + b) * 4 + (h & 3)) * 8 + w8)) * (8 * 96) + (h >> 2) * 96 + lane;
#pragma unroll
  for (int k = 0; k < 3; k++)
    dst[k * 32] = make_uint4(pack_bf16(acc[8 * k], acc[8 * k + 1]), pack_bf16(acc[8 * k + 2], acc[8 * k + 3]),
                             pack_bf16(acc[8 * k + 4], acc[8 * k + 5]), pack_bf16(acc[8 * k + 6], acc[8 * k + 7]));
}

template <int MODE>
__device__ __forceinline__ void finalize(uint32_t sm, uint32_t bars, GCur<MODE>& cur, bf16* out, int br, int q) {
  const int tid = opaque_tid(), cta = opaque_cta();
  const int t256 = tid - 128;
  const int h = cta >> 2;
  bf16* dst = out + (size_t)((4 * (cta & 3) + q) * SQ) * 1024 + br * 512 + (h & 3) * 128 + (h >> 2) * 16;
  mbar_wait(bars, cur.full(), cur.phase);
  const uint32_t b0 = sm + cur.off(); const int e0 = cur.empty(); cur.next();
  if (t256 < 192) {
    const int rp = t256 >> 3, c = (t256 & 7) * 2;
    const int wi = 2 * (rp >> 2) + (c >> 3);
    const uint32_t a0 = b0 + ((wi >> 2) * 32 + (c & 7) * 4 + (rp & 3)) * 16 + (wi & 3) * 4;
    float s00 = 0.f, s01 = 0.f, s10 = 0.f, s11 = 0.f;
#pragma unroll
    for (int p = 0; p < 8; p++) {
      uint32_t x0, x1;
      asm volatile("ld.shared.u32 %0, [%1];" : "=r"(x0) : "r"(a0 + p * 1536));
      asm volatile("ld.shared.u32 %0, [%1+64];" : "=r"(x1) : "r"(a0 + p * 1536));
      s00 += __uint_as_float(x0 << 16); s10 += __uint_as_float(x0 & 0xffff0000u);
      s01 += __uint_as_float(x1 << 16); s11 += __uint_as_float(x1 & 0xffff0000u);
    }
    *reinterpret_cast<uint32_t*>(dst + (2 * rp) * 1024 + c) = pack_bf16(s00, s01);
    *reinterpret_cast<uint32_t*>(dst + (2 * rp + 1) * 1024 + c) = pack_bf16(s10, s11);
  }
  __syncwarp();
  if ((tid & 31) == 0) mbar_arrive(bars + e0 * 8);
}

__device__ __forceinline__ void gemm_qp(uint32_t sm, uint32_t bars, GCur<0>& gc) {
  uint32_t wf[WREG][4];
  if (threadIdx.x == 128) TSTAMP(16);
  {
    GCur<2> wc; wc.init(0);
    mbar_wait(bars, B_WQF, 0);
    if (threadIdx.x == 128) TSTAMP(25);
    load_w<2>(wf, sm, bars, wc);
  }
  if (threadIdx.x == 128) TSTAMP(26);
  mbar_wait(bars, B_WSF, 0);
  if (threadIdx.x == 128) TSTAMP(27);
  mbar_wait(bars, B_GF, 0);
  if (threadIdx.x == 128) TSTAMP(28);
#pragma unroll 1
  for (int i = 0; i < 8; i++) {
    float acc[24];
    brick<0>(acc, wf, sm, bars, gc);
    const bool leader = (opaque_tid() & 31) == 0;
    if (i == 7 && leader) mbar_arrive(bars + B_WSE * 8);
    epi_q(acc, i);
    __syncwarp();
    if (leader) mbar_arrive(bars + (B_EVG + i) * 8);
    if (threadIdx.x == 128) TSTAMP(17 + i);
  }
}
__device__ __forceinline__ void gemm_op_a(uint32_t sm, uint32_t bars, GCur<0>& gc) {
  uint32_t wf[WREG][4];
  if (threadIdx.x == 128) TSTAMP(32);
  load_w<0>(wf, sm, bars, gc);
  mbar_wait(bars, B_WSF, 1);
#pragma unroll 1
  for (int s = 0; s < 4; s++) {
    float acc[24];
    brick<0>(acc, wf, sm, bars, gc);
    const bool leader = (opaque_tid() & 31) == 0;
    if (s == 3 && leader) mbar_arrive(bars + B_WSE * 8);
    epi_part(acc, 0, s);
    __syncwarp();
    if (leader) mbar_arrive(bars + (B_EVG + 8 + s) * 8);
    if (threadIdx.x == 128) TSTAMP(33 + s);
  }
}
__device__ __forceinline__ void gemm_op_b(uint32_t sm, uint32_t bars, GCur<0>& gc, bf16* out) {
  uint32_t wf[WREG][4];
  if (threadIdx.x == 128) TSTAMP(40);
  load_w<0>(wf, sm, bars, gc);
  mbar_wait(bars, B_WSF, 0);
  GCur<1> xc; xc.init(0);
#pragma unroll 1
  for (int s = 0; s < 4; s++) {
    float acc[24];
    brick<1>(acc, wf, sm, bars, xc);
    epi_part(acc, 1, s);
    __syncwarp();
    if ((opaque_tid() & 31) == 0) mbar_arrive(bars + (B_EVG + 12 + s) * 8);
    if (threadIdx.x == 128) TSTAMP(41 + s);
    if (s >= 2) {
#pragma unroll 1
      for (int f = 0; f < 4; f++) finalize<1>(sm, bars, xc, out, s - 2, f);
    }
  }
}

__device__ __forceinline__ void gemm_op_phased(uint32_t sm, uint32_t bars, bf16* out) {
  GCur<1> xc; xc.init(0);
#pragma unroll 1
  for (int br = 0; br < 2; br++) {
    uint32_t wf[WREG][4];
    if (threadIdx.x == 128) TSTAMP(32 + br * 8);
    load_w<1>(wf, sm, bars, xc);
    mbar_wait(bars, B_WSF, (br + 1) & 1);
#pragma unroll 1
    for (int s = 0; s < 4; s++) {
      float acc[24];
      brick<1>(acc, wf, sm, bars, xc);
      const bool leader = (opaque_tid() & 31) == 0;
      if (s == 3 && leader) mbar_arrive(bars + B_WSE * 8);
      epi_part(acc, br, s);
      __syncwarp();
      if (leader) mbar_arrive(bars + (B_EVG + 8 + br * 4 + s) * 8);
      if (threadIdx.x == 128) TSTAMP(33 + br * 8 + s);
    }
  }
#pragma unroll 1
  for (int f = 0; f < 8; f++) finalize<1>(sm, bars, xc, out, f >> 2, f & 3);
}

__global__ void __launch_bounds__(NTHREADS, 1) fused_kernel(const __grid_constant__ Params P) {
  extern __shared__ uint8_t smem_raw[];
  const uint32_t sm = (smem_u32(smem_raw) + 1023u) & ~1023u;
  const uint32_t bars = sm + SM_BAR;
  const int tid = threadIdx.x, wg = tid >> 7, warp = (tid >> 5) & 3, lane = tid & 31;
  const int cta = blockIdx.x;
  const int h = cta >> 2, j = cta & 3;
  const int n_t = h & 3, kc = h >> 2;

  if (tid == 0) {
    TSTAMP(0);
    asm volatile("st.shared.u32 [%0], %1;" ::"r"(bars + B_END * 8 + 8), "r"((uint32_t)clock()) : "memory");
  }
  if (tid < B_END) {
    int cnt = 1;
    if (tid >= B_KVE && tid < B_GF) cnt = 12;
    else if (tid >= B_GE && tid < B_EVA) cnt = 8;
    else if (tid >= B_EVA && tid < B_WSF) cnt = (tid == B_EVA + 1) ? 12 : 4;
    else if (tid == B_WSE || tid == B_WQE) cnt = 8;
    else if (tid >= B_XE && tid < B_RDY) cnt = 8;
    mbar_init(bars + tid * 8, cnt);
    asm volatile("fence.mbarrier_init.release.cluster;" ::: "memory");
  }
  __syncthreads();

  if (wg == 3) {
    asm volatile("setmaxnreg.dec.sync.aligned.u32 32;");
    if (warp == 0 && lane == 0) {
      prefetch_tmap(&P.kB); prefetch_tmap(&P.vB); prefetch_tmap(&P.qB);
      prefetch_tmap(&P.kA); prefetch_tmap(&P.vA); prefetch_tmap(&P.qA);
      for (int u = 0; u < 5; u++) {
        const bool isA = (u == 1);
        const int s = u == 0 ? 0 : u - 1;
        const size_t off = isA ? (size_t)((4 * j + (h & 3)) * NGRP + kc) * SK * DH : (size_t)((4 * j + s) * NH + h) * SK * DH;
        touch_page((isA ? P.pkA : P.pkB) + off);
        touch_page((isA ? P.pvA : P.pvB) + off);
      }
      mbar_wait(bars, B_WQE, 0);
      const uint64_t pol = policy_evict_first();
      Cursor<NKVS> c; c.init(0);
#pragma unroll 1
      for (int u = 0; u < 5; u++) {
        const bool isA = (u == 1);
        const int s = u == 0 ? 0 : u - 1;
        const int b = isA ? 4 * j + (h & 3) : 4 * j + s;
        const int nq = 1;
        const CUtensorMap* mk_ = isA ? &P.kA : &P.kB;
        const CUtensorMap* mv_ = isA ? &P.vA : &P.vB;
        const CUtensorMap* mq_ = isA ? &P.qA : &P.qB;
        const int row0 = isA ? (b * NGRP + kc) * SK : (b * NH + h) * SK;
        const int qrow0 = isA ? (b * NGRP + kc) * 192 : (b * NH + h) * SQ;
        Cursor<NKVS> qc = c;
        for (int i = 0; i < nq; i++) { mbar_wait(bars, B_KVE + c.slot, c.phase ^ 1); c.next(); }
        bool qdone = false;
#pragma unroll 1
        for (int t = 0; t < 16; t++) {
          if (!qdone) {
            while (true) {
              if (mbar_test(bars + (B_RDY + u) * 8, 0)) {
                for (int i = 0; i < nq; i++) {
                  mbar_expect_tx(bars + (B_KVF + qc.slot) * 8, SLOT);
                  tma_3d(sm + SM_KV + qc.slot * SLOT, mq_, 0, qrow0 + i * 64, 0, bars + (B_KVF + qc.slot) * 8);
                  qc.next();
                }
                qdone = true;
                break;
              }
              if (mbar_test(bars + (B_KVE + c.slot) * 8, c.phase ^ 1)) break;
              if (expired(bars)) break;
              __nanosleep(100);
            }
          }
          mbar_wait(bars, B_KVE + c.slot, c.phase ^ 1);
          mbar_expect_tx(bars + (B_KVF + c.slot) * 8, SLOT);
          tma_3d_hint(sm + SM_KV + c.slot * SLOT, (t & 1) ? mv_ : mk_, 0, row0 + (t >> 1) * 64, 0, bars + (B_KVF + c.slot) * 8, pol);
          c.next();
        }
      }
    } else if (warp == 1 && lane == 0) {
      prefetch_tmap(&P.wqB); prefetch_tmap(&P.xB); prefetch_tmap(&P.wqA); prefetch_tmap(&P.xA);
      prefetch_tmap(&P.woA); prefetch_tmap(&P.oA); prefetch_tmap(&P.woB); prefetch_tmap(&P.oB);
      touch_page(P.pwoA + (size_t)kc * 512 * 512);
      touch_page(P.pwoB + (size_t)kc * 512 * 512);
      touch_page(g_OA + (size_t)(4 * j * SQ) * 4096);
      touch_page(g_OB + (size_t)(4 * j * SQ) * 4096);
      touch_page(g_OA + (size_t)((4 * j + 3) * SQ + 47) * 4096);
      touch_page(g_OB + (size_t)((4 * j + 3) * SQ + 47) * 4096);
      for (int q = 0; q < 8; q++) touch_page(g_part + ((size_t)((((q >> 2) * NB + 4 * j + (q & 3)) * 4 + n_t) * 8 + kc)) * (8 * 96));
      TSTAMP(29);
      GCur<0> c; c.init(0);
      uint32_t wsph = 1;
      auto ldWS = [&](const CUtensorMap* mt, int k0, int nch) {
        mbar_wait(bars, B_WSE, wsph);
        wsph ^= 1;
        mbar_expect_tx(bars + B_WSF * 8, (32 - WREG) * 4096);
        tma_3d(sm + SM_WS, mt, 0, k0 + WREG * 16, nch, bars + B_WSF * 8);
      };
      auto ldW = [&](const CUtensorMap* m, const CUtensorMap* mt, int k0, int nch) {
        for (int i = 0; i < WREG / 3; i++) {
          if (i == NGS) ldWS(mt, k0, nch);
          mbar_wait(bars, c.empty(), c.phase ^ 1);
          mbar_expect_tx(bars + c.full() * 8, XBYTES);
          tma_3d(sm + c.off(), m, 0, k0 + i * 48, nch, bars + c.full() * 8);
          c.next();
        }
      };
      auto ldX = [&](const CUtensorMap* m, int row0, int ch0) {
        for (int i = 0; i < 4; i++) {
          mbar_wait(bars, c.empty(), c.phase ^ 1);
          mbar_expect_tx(bars + c.full() * 8, XBYTES);
          tma_3d(sm + c.off(), m, 0, row0, ch0 + 2 * i, bars + c.full() * 8);
          c.next();
        }
      };
      {
        const CUtensorMap* m = j < 2 ? &P.wqB : &P.wqA;
        GCur<2> wc; wc.init(0);
        for (int i = 0; i < WREG / 3; i++) {
          mbar_expect_tx(bars + wc.full() * 8, XBYTES);
          tma_3d(sm + wc.off(), m, 0, i * 48, 2 * h, bars + wc.full() * 8);
          wc.next();
        }
        ldWS(j < 2 ? &P.wqBt : &P.wqAt, 0, 2 * h);
        TSTAMP(30);
      }
      for (int i = 0; i < 8; i++) ldX(j < 2 ? &P.xB : &P.xA, qp_batch(j, i) * SQ, 0);
      for (int i = 0; i < QPAD; i++) {
        mbar_wait(bars, c.empty(), c.phase ^ 1);
        mbar_arrive(bars + c.full() * 8);
        c.next();
      }
      {
        const int bA = 4 * j + (h & 3);
        mbar_wait(bars, B_RDY + 1, 0);
        GCur<0> c0 = c;
        for (int i = 0; i < 3; i++) { mbar_wait(bars, c.empty(), c.phase ^ 1); c.next(); }
        mbar_expect_tx(bars + c0.full() * 8, 32768);
        tma_3d(sm + c0.off(), &P.qA, 0, (bA * NGRP + kc) * 192 + 64, 0, bars + c0.full() * 8);
        tma_3d(sm + c0.off() + 16384, &P.qA, 0, (bA * NGRP + kc) * 192 + 128, 0, bars + c0.full() * 8);
        mbar_arrive(bars + (c0.full() + 1) * 8);
        mbar_arrive(bars + (c0.full() + 2) * 8);
      }
      ldW(&P.woA, &P.woAt, kc * 512, 2 * n_t);
      for (int s = 0; s < 4; s++) {
        mbar_wait(bars, B_RDY + 5 + s, 0);
        ldX(&P.oA, (4 * j + s) * SQ, kc * 8);
      }
      ldW(&P.woB, &P.woBt, kc * 512, 2 * n_t);
      {
        for (int i = 0; i < NGS; i++) { mbar_wait(bars, c.empty(), c.phase ^ 1); c.next(); }
        GCur<1> x; x.init(0);
        int issued = 0;
        auto acquire = [&]() {
          if (issued == NGS) mbar_wait(bars, B_EVA + 4, 0);
          mbar_wait(bars, x.empty(), x.phase ^ 1);
          issued++;
        };
        for (int s = 0; s < 4; s++) {
          mbar_wait(bars, B_RDY + 9 + s, 0);
          for (int i = 0; i < 4; i++) {
            acquire();
            mbar_expect_tx(bars + x.full() * 8, XBYTES);
            tma_3d(sm + x.off(), &P.oB, 0, (4 * j + s) * SQ, kc * 8 + 2 * i, bars + x.full() * 8);
            x.next();
          }
          if (s >= 2) {
            const int br = s - 2;
            for (int q = 0; q < 4; q++) {
              mbar_wait(bars, B_RDY + 13 + br * 4 + q, 0);
              const uint4* src = g_part + ((size_t)(((br * NB + 4 * j + q) * 4 + n_t) * 8 + kc)) * (8 * 96);
              acquire();
              mbar_expect_tx(bars + x.full() * 8, XBYTES);
              bulk_g2s(sm + x.off(), src, XBYTES, bars + x.full() * 8);
              x.next();
            }
          }
        }
      }
    } else if (warp == 2) {
      if (lane < 2) {
        const int nev = lane == 0 ? 16 : 5;
        int e = 0;
        while (e < nev) {
          if (mbar_test(bars + ((lane == 0 ? B_EVG : B_EVA) + e) * 8, 0)) {
            __threadfence();
            unsigned* f;
            if (lane == 0) {
              if (e < 8) {
                const int b = qp_batch(j, e);
                f = (j < 2) ? &g_flags.qb_flag[(b * NH + h) * 8] : &g_flags.qa_cnt[(b * NGRP + kc) * 8];
              } else {
                f = &g_flags.part_cnt[(((e < 12 ? 0 : 1) * NB + 4 * j + (e & 3)) * 4 + n_t) * 8];
              }
            } else {
              f = (e == 1) ? &g_flags.oa_cnt[((4 * j + (h & 3)) * NGRP + kc) * 8]
                           : &g_flags.ob_cnt[((4 * j + (e == 0 ? 0 : e - 1)) * NGRP + kc) * 8];
            }
            red_add(f, 1);
            e++;
          } else {
            if (expired(bars)) break;
            __nanosleep(POLL_NS);
          }
        }
      }
    } else if (warp == 3) {
      unsigned ep1 = 0;
      if (lane == 0) {
        const unsigned e = *reinterpret_cast<volatile unsigned*>(&g_flags.epoch);
        ep1 = e + 1;
        __threadfence();
        const unsigned old = atomicAdd(&g_flags.started, 1u);
        if (old == gridDim.x - 1) {
          g_flags.started = 0;
          __threadfence();
          *reinterpret_cast<volatile unsigned*>(&g_flags.epoch) = e + 1;
        }
      }
      ep1 = __shfl_sync(0xffffffffu, ep1, 0);
      if (lane < 21) {
        const unsigned* f;
        unsigned target;
        if (lane < 5) {
          if (lane == 1) { f = &g_flags.qa_cnt[((4 * j + (h & 3)) * NGRP + kc) * 8]; target = 4 * ep1; }
          else { f = &g_flags.qb_flag[((4 * j + (lane == 0 ? 0 : lane - 1)) * NH + h) * 8]; target = ep1; }
        } else if (lane < 9) { f = &g_flags.oa_cnt[((4 * j + lane - 5) * NGRP + kc) * 8]; target = ep1; }
        else if (lane < 13) { f = &g_flags.ob_cnt[((4 * j + lane - 9) * NGRP + kc) * 8]; target = 4 * ep1; }
        else { f = &g_flags.part_cnt[((((lane - 13) >> 2) * NB + 4 * j + ((lane - 13) & 3)) * 4 + n_t) * 8]; target = 8 * ep1; }
        bool done = false;
        while (true) {
          if (!done && (int)(ld_acquire(f) - target) >= 0) {
            fence_proxy_async_global();
            mbar_arrive(bars + (B_RDY + lane) * 8);
            done = true;
          }
          if (__all_sync(0x1fffffu, done)) break;
          if (__any_sync(0x1fffffu, expired(bars))) break;
          __nanosleep(POLL_NS);
        }
      }
    }
  } else {
    asm volatile("setmaxnreg.inc.sync.aligned.u32 160;");
    if (wg == 0) {
      Cursor<NKVS> cur; cur.init(0);
      if (tid == 0) TSTAMP(1);
      attn_ss<false, true>(sm, bars, cur, 0, sm + SM_QS);
      signal_unit(bars, 0);
      if (tid == 0) TSTAMP(2);
      if (tid == 0) TSTAMP(3);
      attn_ss<true, true>(sm, bars, cur, 0, sm + SM_QS);
      signal_unit(bars, 1);
      if (tid == 0) TSTAMP(4);
#pragma unroll 1
      for (int u = 2; u < 5; u++) {
        if (tid == 0) TSTAMP(1 + 2 * u);
        attn_ss<false, true>(sm, bars, cur, u - 1, sm + SM_QS);
        signal_unit(bars, u);
        if (tid == 0) TSTAMP(2 + 2 * u);
      }
    } else {
      GCur<0> gc; gc.init(0);
      gemm_qp(sm, bars, gc);
      {
        mbar_wait(bars, B_EVA + 0, 0);
        const bool leader = (tid & 31) == 0;
        for (int i = 0; i < QPAD; i++) {
          mbar_wait(bars, gc.full(), gc.phase);
          if (leader) mbar_arrive(bars + gc.empty() * 8);
          gc.next();
        }
        const uint32_t q0 = gc.off();
        const int e0 = gc.empty();
        for (int i = 0; i < 3; i++) { mbar_wait(bars, gc.full(), gc.phase); gc.next(); }
        Cursor<NKVS> cur; cur.init(17);
        attn_ss<true, false>(sm, bars, cur, 0, sm + q0 + (wg - 1) * 16384);
        if (leader) for (int i = 0; i < 3; i++) mbar_arrive(bars + (e0 + i) * 8);
        signal_unit(bars, 1);
      }
      gemm_op_a(sm, bars, gc);
      gemm_op_b(sm, bars, gc, P.out);
      if (tid == 128) TSTAMP(48);
    }
  }
}

typedef CUresult (*EncodeFn)(CUtensorMap*, CUtensorMapDataType, cuuint32_t, void*, const cuuint64_t*, const cuuint64_t*,
                             const cuuint32_t*, const cuuint32_t*, CUtensorMapInterleave, CUtensorMapSwizzle,
                             CUtensorMapL2promotion, CUtensorMapFloatOOBfill);

static bool make_map(EncodeFn fn, CUtensorMap* m, const void* base, uint64_t rows, uint64_t row_elems, uint32_t box_rows,
                     uint32_t box_depth = 2) {
  cuuint64_t dims[3] = {64, rows, row_elems / 64};
  cuuint64_t strides[2] = {row_elems * 2, 128};
  cuuint32_t box[3] = {64, box_rows, box_depth};
  cuuint32_t estr[3] = {1, 1, 1};
  CUresult r = fn(m, CU_TENSOR_MAP_DATA_TYPE_BFLOAT16, 3, const_cast<void*>(base), dims, strides, box, estr,
                  CU_TENSOR_MAP_INTERLEAVE_NONE, CU_TENSOR_MAP_SWIZZLE_128B, CU_TENSOR_MAP_L2_PROMOTION_L2_256B,
                  CU_TENSOR_MAP_FLOAT_OOB_FILL_NONE);
  if (r != CUDA_SUCCESS) fprintf(stderr, "cuTensorMapEncodeTiled failed: %d\n", (int)r);
  return r == CUDA_SUCCESS;
}

}

extern "C" void kernel_launch(void* const* d_in, const int* in_sizes, int n_in, void* d_out, int out_size) {
  using namespace mk;
  static Params P;
  static bool init = false;
  static void* cached[11] = {0};
  bool same = init;
  for (int i = 0; i < 10; i++) same = same && (cached[i] == d_in[i]);
  same = same && (cached[10] == d_out);
  if (!same) {
    void* fnp = nullptr;
    cudaDriverEntryPointQueryResult qr;
    cudaGetDriverEntryPoint("cuTensorMapEncodeTiled", &fnp, cudaEnableDefault, &qr);
    EncodeFn fn = (EncodeFn)fnp;
    void *qa, *qb, *oa, *ob;
    cudaGetSymbolAddress(&qa, g_QA); cudaGetSymbolAddress(&qb, g_QB);
    cudaGetSymbolAddress(&oa, g_OA); cudaGetSymbolAddress(&ob, g_OB);
    make_map(fn, &P.xA, d_in[0], 768, 512, 48);
    make_map(fn, &P.kA, d_in[1], (uint64_t)NB * NGRP * SK, 128, 64);
    make_map(fn, &P.vA, d_in[2], (uint64_t)NB * NGRP * SK, 128, 64);
    make_map(fn, &P.wqA, d_in[3], 512, 4096, 48);
    make_map(fn, &P.wqAt, d_in[3], 512, 4096, (32 - WREG) * 16);
    make_map(fn, &P.woA, d_in[4], 4096, 512, 48);
    make_map(fn, &P.woAt, d_in[4], 4096, 512, (32 - WREG) * 16);
    make_map(fn, &P.xB, d_in[5], 768, 512, 48);
    make_map(fn, &P.kB, d_in[6], (uint64_t)NB * NH * SK, 128, 64);
    make_map(fn, &P.vB, d_in[7], (uint64_t)NB * NH * SK, 128, 64);
    make_map(fn, &P.wqB, d_in[8], 512, 4096, 48);
    make_map(fn, &P.wqBt, d_in[8], 512, 4096, (32 - WREG) * 16);
    make_map(fn, &P.woB, d_in[9], 4096, 512, 48);
    make_map(fn, &P.woBt, d_in[9], 4096, 512, (32 - WREG) * 16);
    make_map(fn, &P.qA, qa, (uint64_t)NB * NGRP * 192, 128, 64);
    make_map(fn, &P.qB, qb, (uint64_t)NB * NH * SQ + 16, 128, 64);
    make_map(fn, &P.oA, oa, 768, 4096, 48);
    make_map(fn, &P.oB, ob, 768, 4096, 48);
    P.out = (bf16*)d_out;
    P.pkA = (const bf16*)d_in[1]; P.pvA = (const bf16*)d_in[2]; P.pwoA = (const bf16*)d_in[4];
    P.pkB = (const bf16*)d_in[6]; P.pvB = (const bf16*)d_in[7]; P.pwoB = (const bf16*)d_in[9];
    cudaFuncSetAttribute(fused_kernel, cudaFuncAttributeMaxDynamicSharedMemorySize, SM_TOTAL);
    for (int i = 0; i < 10; i++) cached[i] = d_in[i];
    cached[10] = d_out;
    init = true;
  }
  fused_kernel<<<NCTA, NTHREADS, SM_TOTAL>>>(P);
}
```

```cpp
#include <cuda_runtime.h>
#include <cuda_bf16.h>
#include <cuda.h>
#include <stdint.h>
#include <stdio.h>
#include <stdlib.h>

namespace mk {

typedef __nv_bfloat16 bf16;

constexpr int NB = 16, SQ = 48, NH = 32, NGRP = 8, SK = 512, DH = 128;
constexpr int SLOT = 16384;
#define NKVS 8
#define NGS 5
#define KVGO -1
#define POLL_NS 64
#define WAIT_HINT_NS 100000u
constexpr int XBYTES = 12288;
constexpr int WREG = 27;
constexpr int SM_QS = 0;
constexpr int SM_KV = 16384;
constexpr int SM_G = SM_KV + NKVS * SLOT;
constexpr int SM_WS = SM_G + NGS * XBYTES;
constexpr int SM_BAR = SM_WS + (32 - WREG) * 4096;
constexpr int SM_TOTAL = SM_BAR + 1024 + 1024;
constexpr int NEXT = (NKVS * SLOT) / XBYTES;
constexpr int NWIDE = NGS + NEXT;
constexpr int SM_EXT = SM_G - NEXT * XBYTES;
static_assert(NEXT >= WREG / 3, "the first weight tile is loaded into the extra slots");
constexpr int QP_ENTRIES = 8 * 4 + WREG / 3;
#define UA_POS 3
constexpr int UA = UA_POS;
constexpr int KV_POS_A = 16 + 17 * (UA - 1);
constexpr int QPAD = (QP_ENTRIES % NGS + 3 > NGS) ? NGS - QP_ENTRIES % NGS : 0;
constexpr int NCTA = 128;
constexpr int NTHREADS = 512;

constexpr int B_KVF = 0;
constexpr int B_KVE = B_KVF + NKVS;
constexpr int B_GF = B_KVE + NKVS;
constexpr int B_GE = B_GF + NGS;
constexpr int B_EVG = B_GE + NGS;
constexpr int B_EVA = B_EVG + 16;
constexpr int B_WSF = B_EVA + 5;
constexpr int B_WSE = B_WSF + 1;
constexpr int B_WQF = B_WSE + 1;
constexpr int B_WQE = B_WQF + WREG / 3;
constexpr int B_XF = B_WQE + 1;
constexpr int B_XE = B_XF + NWIDE;
constexpr int B_RDY = B_XE + NWIDE;
constexpr int B_Q0 = B_RDY + 21;
constexpr int B_END = B_Q0 + 1;
static_assert(B_END * 8 + 16 <= 1024 && B_END <= 512, "barrier region");
static_assert(SM_TOTAL <= 232448, "smem");

struct alignas(64) Params {
  CUtensorMap kA, vA, kB, vB, qA, qB;
  CUtensorMap xA, xB, oA, oB;
  CUtensorMap wqA, wqB, woA, woB;
  CUtensorMap wqAt, wqBt, woAt, woBt;
  bf16* out;
};

__device__ bf16 g_QA[NB * NGRP * 192 * DH];
__device__ bf16 g_QB[NB * NH * SQ * DH + 16 * DH];
__device__ bf16 g_OA[NB * SQ * NH * DH];
__device__ bf16 g_OB[NB * SQ * NH * DH];
__device__ uint4 g_part[2 * NB * 4 * 8 * 8 * 96];
struct Flags {
  unsigned epoch;
  unsigned pad0[31];
  unsigned started;
  unsigned pad1[31];
  unsigned qa_cnt[NB * NGRP * 8];
  unsigned oa_cnt[NB * NGRP * 8];
  unsigned ob_cnt[NB * NGRP * 8];
  unsigned part_cnt[2 * NB * 4 * 8];
};
__device__ Flags g_flags;
__constant__ uint32_t c_zero;

#define TSTAMP(idx) do {} while (0)

__device__ __forceinline__ uint32_t smem_u32(const void* p) { return (uint32_t)__cvta_generic_to_shared(p); }
__device__ __forceinline__ void mbar_init(uint32_t bar, uint32_t cnt) {
  asm volatile("mbarrier.init.shared::cta.b64 [%0], %1;" ::"r"(bar), "r"(cnt) : "memory");
}
__device__ __forceinline__ void mbar_expect_tx(uint32_t bar, uint32_t bytes) {
  asm volatile("mbarrier.arrive.expect_tx.shared::cta.b64 _, [%0], %1;" ::"r"(bar), "r"(bytes) : "memory");
}
__device__ __forceinline__ void mbar_arrive(uint32_t bar) {
  asm volatile("mbarrier.arrive.shared::cta.b64 _, [%0];" ::"r"(bar) : "memory");
}
__device__ __forceinline__ void mbar_arrive_n(uint32_t bar, uint32_t n) {
  asm volatile("mbarrier.arrive.shared::cta.b64 _, [%0], %1;" ::"r"(bar), "r"(n) : "memory");
}
__device__ __forceinline__ bool mbar_try(uint32_t bar, uint32_t parity) {
  uint32_t ok;
  asm volatile("{\n.reg .pred p;\nmbarrier.try_wait.parity.shared::cta.b64 p, [%1], %2, %3;\nselp.u32 %0, 1, 0, p;\n}"
               : "=r"(ok) : "r"(bar), "r"(parity), "r"(WAIT_HINT_NS) : "memory");
  return ok != 0;
}
__device__ __forceinline__ bool mbar_test(uint32_t bar, uint32_t parity) {
  uint32_t ok;
  asm volatile("{\n.reg .pred p;\nmbarrier.test_wait.parity.shared::cta.b64 p, [%1], %2;\nselp.u32 %0, 1, 0, p;\n}"
               : "=r"(ok) : "r"(bar), "r"(parity) : "memory");
  return ok != 0;
}
__device__ __forceinline__ bool expired(uint32_t bars) {
  uint32_t t0, t1;
  asm volatile("ld.volatile.shared.u32 %0, [%1];" : "=r"(t0) : "r"(bars + B_END * 8));
  asm volatile("mov.u32 %0, %%clock;" : "=r"(t1));
  return (t1 - t0) > 1900000000u;
}
__device__ __forceinline__ int opaque_tid() {
  int t;
  asm volatile("mov.u32 %0, %%tid.x;" : "=r"(t));
  return t;
}
__device__ __forceinline__ int opaque_cta() {
  int t;
  asm volatile("mov.u32 %0, %%ctaid.x;" : "=r"(t));
  return t;
}
__device__ __forceinline__ void mbar_wait(uint32_t bars, int idx, uint32_t parity) {
  while (!mbar_try(bars + idx * 8, parity)) {
    if (expired(bars)) break;
  }
}
__device__ __forceinline__ unsigned ld_acquire(const unsigned* p) {
  unsigned v;
  asm volatile("ld.acquire.gpu.global.u32 %0, [%1];" : "=r"(v) : "l"(p) : "memory");
  return v;
}
__device__ __forceinline__ void red_add(unsigned* p, unsigned v) {
  asm volatile("red.relaxed.gpu.global.add.u32 [%0], %1;" ::"l"(p), "r"(v) : "memory");
}
__device__ __forceinline__ void fence_proxy_async() { asm volatile("fence.proxy.async.shared::cta;" ::: "memory"); }
__device__ __forceinline__ void fence_proxy_async_global() { asm volatile("fence.proxy.async.global;" ::: "memory"); }
__device__ __forceinline__ void tma_3d(uint32_t dst, const CUtensorMap* map, int c0, int c1, int c2, uint32_t bar) {
  asm volatile(
      "cp.async.bulk.tensor.3d.shared::cluster.global.mbarrier::complete_tx::bytes [%0], [%1, {%3, %4, %5}], [%2];" ::"r"(dst),
      "l"(map), "r"(bar), "r"(c0), "r"(c1), "r"(c2)
      : "memory");
}
__device__ __forceinline__ void tma_3d_hint(uint32_t dst, const CUtensorMap* map, int c0, int c1, int c2, uint32_t bar, uint64_t pol) {
  asm volatile(
      "cp.async.bulk.tensor.3d.shared::cluster.global.mbarrier::complete_tx::bytes.L2::cache_hint [%0], [%1, {%3, %4, %5}], [%2], %6;" ::"r"(dst),
      "l"(map), "r"(bar), "r"(c0), "r"(c1), "r"(c2), "l"(pol)
      : "memory");
}
__device__ __forceinline__ uint64_t policy_evict_first() {
  uint64_t pol;
  asm volatile("createpolicy.fractional.L2::evict_first.b64 %0, 1.0;" : "=l"(pol));
  return pol;
}
__device__ __forceinline__ void bulk_g2s(uint32_t dst, const void* src, uint32_t bytes, uint32_t bar) {
  asm volatile("cp.async.bulk.shared::cluster.global.mbarrier::complete_tx::bytes [%0], [%1], %2, [%3];" ::"r"(dst), "l"(src),
               "r"(bytes), "r"(bar)
               : "memory");
}
__device__ __forceinline__ void prefetch_tmap(const CUtensorMap* map) {
  asm volatile("prefetch.tensormap [%0];" ::"l"(map) : "memory");
}
__device__ __forceinline__ void ldsm_x4_t(uint32_t (&r)[4], uint32_t addr) {
  asm volatile("ldmatrix.sync.aligned.m8n8.x4.trans.shared.b16 {%0,%1,%2,%3}, [%4];"
               : "=r"(r[0]), "=r"(r[1]), "=r"(r[2]), "=r"(r[3]) : "r"(addr) : "memory");
}
__device__ __forceinline__ void stsm_x4(uint32_t addr, uint32_t r0, uint32_t r1, uint32_t r2, uint32_t r3) {
  asm volatile("stmatrix.sync.aligned.m8n8.x4.shared.b16 [%0], {%1,%2,%3,%4};" ::"r"(addr), "r"(r0), "r"(r1), "r"(r2), "r"(r3)
               : "memory");
}
__device__ __forceinline__ uint4 lds128(uint32_t addr) {
  uint4 v;
  asm volatile("ld.shared.v4.u32 {%0,%1,%2,%3}, [%4];" : "=r"(v.x), "=r"(v.y), "=r"(v.z), "=r"(v.w) : "r"(addr) : "memory");
  return v;
}
__device__ __forceinline__ void sts128(uint32_t addr, uint4 v) {
  asm volatile("st.shared.v4.u32 [%0], {%1,%2,%3,%4};" ::"r"(addr), "r"(v.x), "r"(v.y), "r"(v.z), "r"(v.w) : "memory");
}
__device__ __forceinline__ uint32_t dep_on(uint32_t addr, uint32_t loaded) { return addr + (loaded & c_zero); }
__device__ __forceinline__ void named_bar(int id, int n) { asm volatile("bar.sync %0, %1;" ::"r"(id), "r"(n) : "memory"); }
__device__ __forceinline__ void wg_fence() { asm volatile("wgmma.fence.sync.aligned;" ::: "memory"); }
__device__ __forceinline__ void wg_commit() { asm volatile("wgmma.commit_group.sync.aligned;" ::: "memory"); }
template <int N>
__device__ __forceinline__ void wg_wait() { asm volatile("wgmma.wait_group.sync.aligned %0;" ::"n"(N) : "memory"); }
template <int N>
__device__ __forceinline__ void fence_regs(float (&a)[N]) {
#pragma unroll
  for (int i = 0; i < N; i++) asm volatile("" : "+f"(a[i])::"memory");
}
__device__ __forceinline__ uint64_t make_desc(uint32_t addr, uint32_t lbo, uint32_t sbo) {
  return (uint64_t)((addr & 0x3FFFF) >> 4) | ((uint64_t)(lbo >> 4) << 16) | ((uint64_t)(sbo >> 4) << 32) | (1ull << 62);
}
__device__ __forceinline__ uint32_t pack_bf16(float lo, float hi) {
  uint32_t r;
  asm("cvt.rn.bf16x2.f32 %0, %1, %2;" : "=r"(r) : "f"(hi), "f"(lo));
  return r;
}
__device__ __forceinline__ float ex2(float x) {
  float y;
  asm("ex2.approx.ftz.f32 %0, %1;" : "=f"(y) : "f"(x));
  return y;
}
__device__ __forceinline__ float rcp(float x) {
  float y;
  asm("rcp.approx.ftz.f32 %0, %1;" : "=f"(y) : "f"(x));
  return y;
}
__device__ __forceinline__ uint32_t movmatrix_t(uint32_t x) {
  uint32_t y;
  asm volatile("movmatrix.sync.aligned.m8n8.trans.b16 %0, %1;" : "=r"(y) : "r"(x));
  return y;
}

#define ACC8(d, o) "+f"(d[o]), "+f"(d[o + 1]), "+f"(d[o + 2]), "+f"(d[o + 3]), "+f"(d[o + 4]), "+f"(d[o + 5]), "+f"(d[o + 6]), "+f"(d[o + 7])
__device__ __forceinline__ void wgmma_n64_ss(float (&d)[32], uint64_t da, uint64_t db, int scale_d) {
  asm volatile(
      "{\n.reg .pred p;\nsetp.ne.b32 p, %34, 0;\n"
      "wgmma.mma_async.sync.aligned.m64n64k16.f32.bf16.bf16 "
      "{%0,%1,%2,%3,%4,%5,%6,%7,%8,%9,%10,%11,%12,%13,%14,%15,%16,%17,%18,%19,%20,%21,%22,%23,%24,%25,%26,%27,%28,%29,%30,%31},"
      "%32, %33, p, 1, 1, 0, 0;\n}"
      : ACC8(d, 0), ACC8(d, 8), ACC8(d, 16), ACC8(d, 24)
      : "l"(da), "l"(db), "r"(scale_d));
}
__device__ __forceinline__ void wgmma_n128_t(float (&d)[64], const uint32_t (&a)[4], uint64_t desc, int scale_d) {
  asm volatile(
      "{\n.reg .pred p;\nsetp.ne.b32 p, %69, 0;\n"
      "wgmma.mma_async.sync.aligned.m64n128k16.f32.bf16.bf16 "
      "{%0,%1,%2,%3,%4,%5,%6,%7,%8,%9,%10,%11,%12,%13,%14,%15,%16,%17,%18,%19,%20,%21,%22,%23,%24,%25,%26,%27,%28,%29,%30,%31,"
      "%32,%33,%34,%35,%36,%37,%38,%39,%40,%41,%42,%43,%44,%45,%46,%47,%48,%49,%50,%51,%52,%53,%54,%55,%56,%57,%58,%59,%60,%61,%62,%63},"
      "{%64,%65,%66,%67}, %68, p, 1, 1, 1;\n}"
      : ACC8(d, 0), ACC8(d, 8), ACC8(d, 16), ACC8(d, 24), ACC8(d, 32), ACC8(d, 40), ACC8(d, 48), ACC8(d, 56)
      : "r"(a[0]), "r"(a[1]), "r"(a[2]), "r"(a[3]), "l"(desc), "r"(scale_d));
}
__device__ __forceinline__ void wgmma_n48(float (&d)[24], const uint32_t (&a)[4], uint64_t desc, int scale_d) {
  asm volatile(
      "{\n.reg .pred p;\nsetp.ne.b32 p, %29, 0;\n"
      "wgmma.mma_async.sync.aligned.m64n48k16.f32.bf16.bf16 "
      "{%0,%1,%2,%3,%4,%5,%6,%7,%8,%9,%10,%11,%12,%13,%14,%15,%16,%17,%18,%19,%20,%21,%22,%23},"
      "{%24,%25,%26,%27}, %28, p, 1, 1, 0;\n}"
      : ACC8(d, 0), ACC8(d, 8), ACC8(d, 16)
      : "r"(a[0]), "r"(a[1]), "r"(a[2]), "r"(a[3]), "l"(desc), "r"(scale_d));
}
__device__ __forceinline__ void wgmma_n48_ss(float (&d)[24], uint64_t descA, uint64_t descB) {
  asm volatile(
      "{\n.reg .pred p;\nsetp.ne.b32 p, 1, 0;\n"
      "wgmma.mma_async.sync.aligned.m64n48k16.f32.bf16.bf16 "
      "{%0,%1,%2,%3,%4,%5,%6,%7,%8,%9,%10,%11,%12,%13,%14,%15,%16,%17,%18,%19,%20,%21,%22,%23},"
      "%24, %25, p, 1, 1, 1, 0;\n}"
      : ACC8(d, 0), ACC8(d, 8), ACC8(d, 16)
      : "l"(descA), "l"(descB));
}

struct KCur {
  int slot;
  uint32_t phase;
  __device__ __forceinline__ void init(int count) { slot = count % NKVS; phase = (count / NKVS) & 1; }
  __device__ __forceinline__ void next() { if (++slot == NKVS) { slot = 0; phase ^= 1; } }
};
template <int MODE>
struct GCur {
  int slot;
  uint32_t phase;
  static constexpr int N = MODE == 0 ? NGS : (MODE == 1 ? NWIDE : WREG / 3);
  __device__ __forceinline__ void init(int count) { slot = count % N; phase = (count / N) & 1; }
  __device__ __forceinline__ void next() { if (++slot == N) { slot = 0; phase ^= 1; } }
  __device__ __forceinline__ uint32_t off() const {
    if (MODE == 0) return SM_G + slot * XBYTES;
    if (MODE == 1) return SM_EXT + (slot < NGS ? slot + NEXT : slot - NGS) * XBYTES;
    return SM_EXT + slot * XBYTES;
  }
  __device__ __forceinline__ int full() const { return (MODE == 0 ? B_GF : (MODE == 1 ? B_XF : B_WQF)) + slot; }
  __device__ __forceinline__ int empty() const { return MODE == 2 ? B_WQE : (MODE == 0 ? B_GE : B_XE) + slot; }
};

constexpr float SM_C = 0.08838834764831845f * 1.4426950408889634f;
constexpr float RESCALE_T = 8.0f;

__device__ __forceinline__ void softmax_step(const float (&s)[32], uint32_t (&pf)[4][4], float (&o)[64], float& m0, float& m1,
                                             float& l0, float& l1, bool first) {
  float mx0 = fmaxf(s[0], s[1]), mx1 = fmaxf(s[2], s[3]);
#pragma unroll
  for (int j = 1; j < 8; j++) {
    mx0 = fmaxf(mx0, fmaxf(s[4 * j], s[4 * j + 1]));
    mx1 = fmaxf(mx1, fmaxf(s[4 * j + 2], s[4 * j + 3]));
  }
  mx0 = fmaxf(mx0, __shfl_xor_sync(0xffffffffu, mx0, 1));
  mx1 = fmaxf(mx1, __shfl_xor_sync(0xffffffffu, mx1, 1));
  mx0 = fmaxf(mx0, __shfl_xor_sync(0xffffffffu, mx0, 2));
  mx1 = fmaxf(mx1, __shfl_xor_sync(0xffffffffu, mx1, 2));
  const bool grow = !((mx0 - m0) * SM_C <= RESCALE_T) || !((mx1 - m1) * SM_C <= RESCALE_T);
  if (__any_sync(0xffffffffu, grow)) {
    const float mn0 = fmaxf(m0, mx0), mn1 = fmaxf(m1, mx1);
    const float a0 = ex2((m0 - mn0) * SM_C), a1 = ex2((m1 - mn1) * SM_C);
    m0 = mn0; m1 = mn1;
    l0 *= a0; l1 *= a1;
    if (!first) {
#pragma unroll
      for (int j = 0; j < 16; j++) {
        o[4 * j] *= a0; o[4 * j + 1] *= a0; o[4 * j + 2] *= a1; o[4 * j + 3] *= a1;
      }
    }
  }
  const float mc0 = m0 * SM_C, mc1 = m1 * SM_C;
#pragma unroll
  for (int j = 0; j < 8; j++) {
    const float p0 = ex2(fmaf(s[4 * j], SM_C, -mc0)), p1 = ex2(fmaf(s[4 * j + 1], SM_C, -mc0));
    const float p2 = ex2(fmaf(s[4 * j + 2], SM_C, -mc1)), p3 = ex2(fmaf(s[4 * j + 3], SM_C, -mc1));
    l0 += p0 + p1; l1 += p2 + p3;
    pf[j >> 1][(j & 1) * 2 + 0] = pack_bf16(p0, p1);
    pf[j >> 1][(j & 1) * 2 + 1] = pack_bf16(p2, p3);
  }
}

__device__ __forceinline__ void attn_unit(uint32_t sm, uint32_t bars, KCur& cur, int u, uint32_t qs) {
  const int tid_ = opaque_tid();
  const bool leader = (tid_ & 31) == 0;
  const bool isA = (u == UA);
  const uint32_t narr = isA ? 1 : 3;
  const bool active = isA || (tid_ >> 5) < 3;
  if (u == 0) {
    mbar_wait(bars, B_Q0, 0);
  } else {
    mbar_wait(bars, B_KVF + cur.slot, cur.phase);
    uint32_t rel = bars + (B_KVE + cur.slot) * 8;
    if (tid_ < 128) {
      named_bar(1, 128);
      const uint32_t src = sm + SM_KV + cur.slot * SLOT + tid_ * 16, dst = qs + tid_ * 16;
      uint32_t x = 0;
#pragma unroll
      for (int i = 0; i < 8; i++) {
        const uint4 v = lds128(src + i * 2048);
        sts128(dst + i * 2048, v);
        x ^= v.x;
      }
      rel = dep_on(rel, x);
      fence_proxy_async();
      named_bar(1, 128);
    }
    if (leader) mbar_arrive_n(rel, narr);
    cur.next();
  }
  float o[64];
  float s[32];
  float m0 = -INFINITY, m1 = -INFINITY, l0 = 0.f, l1 = 0.f;
  mbar_wait(bars, B_KVF + cur.slot, cur.phase);
  wg_fence();
#pragma unroll
  for (int ks = 0; ks < 8; ks++)
    wgmma_n64_ss(s, make_desc(qs + (ks >> 2) * 8192 + (ks & 3) * 32, 16, 1024),
                 make_desc(sm + SM_KV + cur.slot * SLOT + (ks >> 2) * 8192 + (ks & 3) * 32, 16, 1024), ks > 0);
  wg_commit();
  wg_wait<0>();
  fence_regs(s);
  if (leader) mbar_arrive_n(bars + (B_KVE + cur.slot) * 8, narr);
  cur.next();
#pragma unroll 1
  for (int t = 0; t < 8; t++) {
    uint32_t pf[4][4];
    if (active) softmax_step(s, pf, o, m0, m1, l0, l1, t == 0);
    else {
#pragma unroll
      for (int k = 0; k < 4; k++) { pf[k][0] = 0; pf[k][1] = 0; pf[k][2] = 0; pf[k][3] = 0; }
    }
    const int vs = cur.slot; const uint32_t vp = cur.phase; cur.next();
    mbar_wait(bars, B_KVF + vs, vp);
    wg_fence();
#pragma unroll
    for (int kk = 0; kk < 4; kk++)
      wgmma_n128_t(o, pf[kk], make_desc(sm + SM_KV + vs * SLOT + kk * 2048, 8192, 1024), (t > 0) || (kk > 0));
    wg_commit();
    if (t < 7) {
      const int ks_ = cur.slot;
      mbar_wait(bars, B_KVF + ks_, cur.phase);
      cur.next();
      wg_fence();
#pragma unroll
      for (int ks = 0; ks < 8; ks++)
        wgmma_n64_ss(s, make_desc(qs + (ks >> 2) * 8192 + (ks & 3) * 32, 16, 1024),
                     make_desc(sm + SM_KV + ks_ * SLOT + (ks >> 2) * 8192 + (ks & 3) * 32, 16, 1024), ks > 0);
      wg_commit();
      wg_wait<1>();
      if (leader) mbar_arrive_n(bars + (B_KVE + vs) * 8, narr);
      wg_wait<0>();
      if (leader) mbar_arrive_n(bars + (B_KVE + ks_) * 8, narr);
    } else {
      wg_wait<0>();
      if (leader) mbar_arrive_n(bars + (B_KVE + vs) * 8, narr);
    }
    fence_regs(s); fence_regs(o);
  }
  if (active) {
    l0 += __shfl_xor_sync(0xffffffffu, l0, 1); l1 += __shfl_xor_sync(0xffffffffu, l1, 1);
    l0 += __shfl_xor_sync(0xffffffffu, l0, 2); l1 += __shfl_xor_sync(0xffffffffu, l1, 2);
    const float i0 = rcp(l0), i1 = rcp(l1);
    const int tid = opaque_tid(), cta = opaque_cta();
    const int lane = tid & 31, w4 = (tid >> 5) & 3;
    named_bar(2 + (tid >> 7), isA ? 128 : 96);
    const uint32_t stg = qs + w4 * 4096;
    {
      const int mi = lane >> 3, row = (mi & 1) * 8 + (lane & 7);
#pragma unroll
      for (int jp = 0; jp < 8; jp++) {
        const int chunk = 2 * jp + (mi >> 1);
        stsm_x4(stg + row * 256 + ((chunk ^ (row & 7)) << 4), pack_bf16(o[8 * jp] * i0, o[8 * jp + 1] * i0),
                pack_bf16(o[8 * jp + 2] * i1, o[8 * jp + 3] * i1), pack_bf16(o[8 * jp + 4] * i0, o[8 * jp + 5] * i0),
                pack_bf16(o[8 * jp + 6] * i1, o[8 * jp + 7] * i1));
      }
    }
    __syncwarp();
    const int h = cta >> 2, jg = cta & 3;
    const int r0 = (tid >> 5) * 16;
    bf16* orow = isA ? g_OA + (size_t)((4 * jg + (h & 3)) * SQ + r0 % SQ) * 4096 + ((h >> 2) * 4 + r0 / SQ) * DH
                     : g_OB + (size_t)((4 * jg + (u < UA ? u : u - 1)) * SQ + r0) * 4096 + h * DH;
#pragma unroll 2
    for (int i = 0; i < 8; i++) {
      const int row = 2 * i + (lane >> 4), chunk = lane & 15;
      const uint4 v = lds128(stg + row * 256 + ((chunk ^ (row & 7)) << 4));
      *reinterpret_cast<uint4*>(orow + (size_t)row * 4096 + chunk * 8) = v;
    }
  }
  __syncwarp();
  if ((opaque_tid() & 31) == 0) mbar_arrive(bars + (B_EVA + u) * 8);
}

template <int MODE>
__device__ __forceinline__ void load_w(uint32_t (&wf)[WREG][4], uint32_t sm, uint32_t bars, GCur<MODE>& cur) {
  const int tid = opaque_tid();
  const int lane = tid & 31, warp = (tid >> 5) & 3, half = (tid >> 7) - 1;
  const int mi = lane >> 3, rr = lane & 7;
  const int chunk = warp * 2 + (mi & 1);
  const uint32_t off = sm + half * 6144 + ((mi >> 1) * 8 + rr) * 128 + ((chunk ^ rr) << 4);
  uint32_t all = 0;
#pragma unroll
  for (int c = 0; c < WREG / 3; c++) {
    mbar_wait(bars, cur.full(), cur.phase);
    const uint32_t base = off + cur.off();
#pragma unroll
    for (int ks = 0; ks < 3; ks++) ldsm_x4_t(wf[c * 3 + ks], base + ks * 2048);
    const uint32_t x = wf[c * 3][0] ^ wf[c * 3 + 1][0] ^ wf[c * 3 + 2][0];
    if (MODE == 2) {
      all ^= x;
    } else {
      const uint32_t rel = dep_on(bars + cur.empty() * 8, x);
      __syncwarp();
      if (lane == 0) mbar_arrive(rel);
    }
    cur.next();
  }
  if (MODE == 2) {
    const uint32_t rel = dep_on(bars + B_WQE * 8, all);
    __syncwarp();
    if (lane == 0) mbar_arrive(rel);
  }
}

template <int MODE>
__device__ __forceinline__ void brick(float (&acc)[24], const uint32_t (&wf)[WREG][4], uint32_t sm, uint32_t bars, GCur<MODE>& cur) {
  int prev_empty = 0;
  const int tid = opaque_tid();
  const bool leader = (tid & 31) == 0;
  const uint32_t ws = sm + SM_WS + ((tid >> 7) - 1) * ((32 - WREG) * 2048);
#pragma unroll
  for (int i = 0; i < 4; i++) {
    mbar_wait(bars, cur.full(), cur.phase);
    const uint32_t base = sm + cur.off();
    wg_fence();
#pragma unroll
    for (int ks = 0; ks < 8; ks++) {
      const uint64_t db = make_desc(base + (ks >> 2) * 6144 + (ks & 3) * 32, 16, 1024);
      if (i * 8 + ks < WREG) wgmma_n48(acc, wf[i * 8 + ks], db, (i > 0) || (ks > 0));
      else wgmma_n48_ss(acc, make_desc(ws + (i * 8 + ks - WREG) * 2048, 8192, 1024), db);
    }
    wg_commit();
    if (i > 0) {
      wg_wait<1>();
      if (leader) mbar_arrive(bars + prev_empty * 8);
    }
    prev_empty = cur.empty();
    cur.next();
  }
  wg_wait<0>();
  fence_regs(acc);
  if (leader) mbar_arrive(bars + prev_empty * 8);
}

__device__ __forceinline__ void epi_q(const float (&acc)[24], int br, int s, uint32_t sm) {
  const int tid = opaque_tid(), cta = opaque_cta();
  const int lane = tid & 31, w8 = (tid >> 5) - 4;
  const int h = cta >> 2, b = 4 * (cta & 3) + s;
  if (br == 1 && s == 0) {
    const uint32_t base = sm + SM_QS + (w8 >> 2) * 8192 + (lane >> 2) * 128 + (lane & 3) * 4;
    const int sw = lane >> 2, ch = (w8 & 3) * 2;
#pragma unroll
    for (int jb = 0; jb < 6; jb++) {
      const uint32_t lo = movmatrix_t(pack_bf16(acc[4 * jb + 0], acc[4 * jb + 1]));
      const uint32_t hi = movmatrix_t(pack_bf16(acc[4 * jb + 2], acc[4 * jb + 3]));
      asm volatile("st.shared.u32 [%0], %1;" ::"r"(base + jb * 1024 + ((ch ^ sw) << 4)), "r"(lo) : "memory");
      asm volatile("st.shared.u32 [%0], %1;" ::"r"(base + jb * 1024 + (((ch + 1) ^ sw) << 4)), "r"(hi) : "memory");
    }
    fence_proxy_async();
    return;
  }
  bf16* dst = br ? g_QB + (size_t)((b * NH + h) * SQ) * DH : g_QA + (size_t)((b * NGRP + (h >> 2)) * 192 + (h & 3) * SQ) * DH;
  bf16* p = dst + w8 * 16 + (lane >> 2) * 128 + (lane & 3) * 2;
#pragma unroll
  for (int jb = 0; jb < 6; jb++) {
    const uint32_t lo = movmatrix_t(pack_bf16(acc[4 * jb + 0], acc[4 * jb + 1]));
    const uint32_t hi = movmatrix_t(pack_bf16(acc[4 * jb + 2], acc[4 * jb + 3]));
    *reinterpret_cast<uint32_t*>(p + jb * 8 * 128) = lo;
    *reinterpret_cast<uint32_t*>(p + jb * 8 * 128 + 8) = hi;
  }
}
__device__ __forceinline__ void epi_part(const float (&acc)[24], int br, int s) {
  const int tid = opaque_tid(), cta = opaque_cta();
  const int lane = tid & 31, w8 = (tid >> 5) - 4;
  const int h = cta >> 2, b = 4 * (cta & 3) + s;
  uint4* dst = g_part + ((size_t)(((br * NB + b) * 4 + (h & 3)) * 8 + w8)) * (8 * 96) + (h >> 2) * 96 + lane;
#pragma unroll
  for (int k = 0; k < 3; k++)
    dst[k * 32] = make_uint4(pack_bf16(acc[8 * k], acc[8 * k + 1]), pack_bf16(acc[8 * k + 2], acc[8 * k + 3]),
                             pack_bf16(acc[8 * k + 4], acc[8 * k + 5]), pack_bf16(acc[8 * k + 6], acc[8 * k + 7]));
}
__device__ __forceinline__ void finalize(uint32_t sm, uint32_t bars, GCur<1>& cur, bf16* out, int br, int q) {
  const int tid = opaque_tid(), cta = opaque_cta();
  const int t256 = tid - 128;
  const int h = cta >> 2;
  bf16* dst = out + (size_t)((4 * (cta & 3) + q) * SQ) * 1024 + br * 512 + (h & 3) * 128 + (h >> 2) * 16;
  mbar_wait(bars, cur.full(), cur.phase);
  const uint32_t b0 = sm + cur.off(); const int e0 = cur.empty(); cur.next();
  if (t256 < 192) {
    const int rp = t256 >> 3, c = (t256 & 7) * 2;
    const int wi = 2 * (rp >> 2) + (c >> 3);
    const uint32_t a0 = b0 + ((wi >> 2) * 32 + (c & 7) * 4 + (rp & 3)) * 16 + (wi & 3) * 4;
    float s00 = 0.f, s01 = 0.f, s10 = 0.f, s11 = 0.f;
#pragma unroll
    for (int p = 0; p < 8; p++) {
      uint32_t x0, x1;
      asm volatile("ld.shared.u32 %0, [%1];" : "=r"(x0) : "r"(a0 + p * 1536));
      asm volatile("ld.shared.u32 %0, [%1+64];" : "=r"(x1) : "r"(a0 + p * 1536));
      s00 += __uint_as_float(x0 << 16); s10 += __uint_as_float(x0 & 0xffff0000u);
      s01 += __uint_as_float(x1 << 16); s11 += __uint_as_float(x1 & 0xffff0000u);
    }
    *reinterpret_cast<uint32_t*>(dst + (2 * rp) * 1024 + c) = pack_bf16(s00, s01);
    *reinterpret_cast<uint32_t*>(dst + (2 * rp + 1) * 1024 + c) = pack_bf16(s10, s11);
  }
  __syncwarp();
  if ((tid & 31) == 0) mbar_arrive(bars + e0 * 8);
}

__device__ __forceinline__ void gemm_qb(uint32_t sm, uint32_t bars, GCur<0>& gc) {
  uint32_t wf[WREG][4];
  {
    GCur<2> wc; wc.init(0);
    load_w<2>(wf, sm, bars, wc);
  }
  mbar_wait(bars, B_WSF, 0);
#pragma unroll 1
  for (int s = 0; s < 4; s++) {
    float acc[24];
    brick<0>(acc, wf, sm, bars, gc);
    const bool leader = (opaque_tid() & 31) == 0;
    if (s == 3 && leader) mbar_arrive(bars + B_WSE * 8);
    epi_q(acc, 1, s, sm);
    __syncwarp();
    if (leader) mbar_arrive(bars + (s == 0 ? B_Q0 : B_EVG + s) * 8);
    if (threadIdx.x == 128) TSTAMP(17 + s);
  }
}
__device__ __forceinline__ void gemm_qa(uint32_t sm, uint32_t bars, GCur<0>& gc) {
  uint32_t wf[WREG][4];
  if (threadIdx.x == 128) TSTAMP(25);
  load_w<0>(wf, sm, bars, gc);
  mbar_wait(bars, B_WSF, 1);
#pragma unroll 1
  for (int s = 0; s < 4; s++) {
    float acc[24];
    brick<0>(acc, wf, sm, bars, gc);
    const bool leader = (opaque_tid() & 31) == 0;
    if (s == 3 && leader) mbar_arrive(bars + B_WSE * 8);
    epi_q(acc, 0, s, sm);
    __syncwarp();
    if (leader) mbar_arrive(bars + (B_EVG + 4 + s) * 8);
    if (threadIdx.x == 128) TSTAMP(21 + s);
  }
}
__device__ __forceinline__ void gemm_op(uint32_t sm, uint32_t bars, bf16* out) {
  GCur<1> xc; xc.init(0);
#pragma unroll 1
  for (int br = 0; br < 2; br++) {
    uint32_t wf[WREG][4];
    if (threadIdx.x == 128) TSTAMP(32 + br * 8);
    load_w<1>(wf, sm, bars, xc);
    mbar_wait(bars, B_WSF, br);
#pragma unroll 1
    for (int s = 0; s < 4; s++) {
      float acc[24];
      brick<1>(acc, wf, sm, bars, xc);
      const bool leader = (opaque_tid() & 31) == 0;
      if (s == 3 && leader) mbar_arrive(bars + B_WSE * 8);
      epi_part(acc, br, s);
      __syncwarp();
      if (leader) mbar_arrive(bars + (B_EVG + 8 + br * 4 + s) * 8);
      if (threadIdx.x == 128) TSTAMP(33 + br * 8 + s);
    }
  }
#pragma unroll 1
  for (int f = 0; f < 8; f++) finalize(sm, bars, xc, out, f >> 2, f & 3);
}

__global__ void __launch_bounds__(NTHREADS, 1) fused_kernel(const __grid_constant__ Params P) {
  extern __shared__ uint8_t smem_raw[];
  const uint32_t sm = (smem_u32(smem_raw) + 1023u) & ~1023u;
  const uint32_t bars = sm + SM_BAR;
  const int tid = threadIdx.x, wg = tid >> 7, warp = (tid >> 5) & 3, lane = tid & 31;
  const int cta = blockIdx.x;
  const int h = cta >> 2, j = cta & 3;
  const int n_t = h & 3, kc = h >> 2;

  if (tid == 0) {
    TSTAMP(0);
    asm volatile("st.shared.u32 [%0], %1;" ::"r"(bars + B_END * 8), "r"((uint32_t)clock()) : "memory");
  }
  if (tid < B_END) {
    int cnt = 1;
    if (tid >= B_KVE && tid < B_GF) cnt = 12;
    else if (tid >= B_GE && tid < B_EVA) cnt = 8;
    else if (tid >= B_EVA && tid < B_WSF) cnt = (tid == B_EVA + UA) ? 12 : 4;
    else if (tid == B_WSE || tid == B_WQE || tid == B_Q0) cnt = 8;
    else if (tid >= B_XE && tid < B_RDY) cnt = 8;
    mbar_init(bars + tid * 8, cnt);
    asm volatile("fence.mbarrier_init.release.cluster;" ::: "memory");
  }
  __syncthreads();

  if (wg == 3) {
    asm volatile("setmaxnreg.dec.sync.aligned.u32 32;");
    if (warp == 0 && lane == 0) {
      prefetch_tmap(&P.kB); prefetch_tmap(&P.vB); prefetch_tmap(&P.qB);
      prefetch_tmap(&P.kA); prefetch_tmap(&P.vA); prefetch_tmap(&P.qA);
      mbar_wait(bars, B_WQE, 0);
      const uint64_t pol = policy_evict_first();
      KCur c; c.init(0);
#pragma unroll 1
      for (int u = 0; u < 5; u++) {
        const bool isA = (u == UA);
        const int b = isA ? 4 * j + (h & 3) : 4 * j + (u < UA ? u : u - 1);
        const CUtensorMap* mk_ = isA ? &P.kA : &P.kB;
        const CUtensorMap* mv_ = isA ? &P.vA : &P.vB;
        const int row0 = isA ? (b * NGRP + kc) * SK : (b * NH + h) * SK;
        const int qslot = c.slot;
        if (u > 0) {
          mbar_wait(bars, B_KVE + c.slot, c.phase ^ 1);
          c.next();
        }
        bool qdone = (u == 0);
#pragma unroll 1
        for (int t = 0; t < 16; t++) {
          while (!qdone) {
            if (mbar_test(bars + (B_RDY + u) * 8, 0)) {
              mbar_expect_tx(bars + (B_KVF + qslot) * 8, SLOT);
              tma_3d(sm + SM_KV + qslot * SLOT, isA ? &P.qA : &P.qB, 0, isA ? (b * NGRP + kc) * 192 : (b * NH + h) * SQ, 0,
                     bars + (B_KVF + qslot) * 8);
              qdone = true;
              break;
            }
            if (mbar_test(bars + (B_KVE + c.slot) * 8, c.phase ^ 1)) break;
            if (expired(bars)) break;
            __nanosleep(64);
          }
          mbar_wait(bars, B_KVE + c.slot, c.phase ^ 1);
          mbar_expect_tx(bars + (B_KVF + c.slot) * 8, SLOT);
          tma_3d_hint(sm + SM_KV + c.slot * SLOT, (t & 1) ? mv_ : mk_, 0, row0 + (t >> 1) * 64, 0, bars + (B_KVF + c.slot) * 8, pol);
          c.next();
        }
      }
    } else if (warp == 1 && lane == 0) {
      prefetch_tmap(&P.wqB); prefetch_tmap(&P.wqBt); prefetch_tmap(&P.xB);
      GCur<0> c; c.init(0);
      uint32_t wsph = 1;
      auto ldWS = [&](const CUtensorMap* mt, int k0, int nch) {
        mbar_wait(bars, B_WSE, wsph);
        wsph ^= 1;
        mbar_expect_tx(bars + B_WSF * 8, (32 - WREG) * 4096);
        tma_3d(sm + SM_WS, mt, 0, k0 + WREG * 16, nch, bars + B_WSF * 8);
      };
      auto ldX = [&](const CUtensorMap* m, int row0, int ch0) {
#pragma unroll 1
        for (int i = 0; i < 4; i++) {
          mbar_wait(bars, c.empty(), c.phase ^ 1);
          mbar_expect_tx(bars + c.full() * 8, XBYTES);
          tma_3d(sm + c.off(), m, 0, row0, ch0 + 2 * i, bars + c.full() * 8);
          c.next();
        }
      };
      auto ldW = [&](const CUtensorMap* m, const CUtensorMap* mt, int k0, int nch) {
#pragma unroll 1
        for (int i = 0; i < WREG / 3; i++) {
          if (i == NGS) ldWS(mt, k0, nch);
          mbar_wait(bars, c.empty(), c.phase ^ 1);
          mbar_expect_tx(bars + c.full() * 8, XBYTES);
          tma_3d(sm + c.off(), m, 0, k0 + i * 48, nch, bars + c.full() * 8);
          c.next();
        }
      };
      {
        GCur<2> wc; wc.init(0);
#pragma unroll 1
        for (int i = 0; i < WREG / 3; i++) {
          mbar_expect_tx(bars + wc.full() * 8, XBYTES);
          tma_3d(sm + wc.off(), &P.wqB, 0, i * 48, 2 * h, bars + wc.full() * 8);
          wc.next();
        }
        ldWS(&P.wqBt, 0, 2 * h);
      }
#pragma unroll 1
      for (int s = 0; s < 4; s++) ldX(&P.xB, (4 * j + s) * SQ, 0);
      prefetch_tmap(&P.wqA); prefetch_tmap(&P.wqAt); prefetch_tmap(&P.xA);
      ldW(&P.wqA, &P.wqAt, 0, 2 * h);
#pragma unroll 1
      for (int s = 0; s < 4; s++) ldX(&P.xA, (4 * j + s) * SQ, 0);
      prefetch_tmap(&P.woA); prefetch_tmap(&P.oA); prefetch_tmap(&P.woB); prefetch_tmap(&P.oB);
      prefetch_tmap(&P.woAt); prefetch_tmap(&P.woBt);
#pragma unroll 1
      for (int i = 0; i < QPAD; i++) {
        mbar_wait(bars, c.empty(), c.phase ^ 1);
        mbar_arrive(bars + c.full() * 8);
        c.next();
      }
      {
        const int bA = 4 * j + (h & 3);
        mbar_wait(bars, B_RDY + UA, 0);
        GCur<0> c0 = c;
#pragma unroll 1
        for (int i = 0; i < 3; i++) { mbar_wait(bars, c.empty(), c.phase ^ 1); c.next(); }
        mbar_expect_tx(bars + c0.full() * 8, 32768);
        tma_3d(sm + c0.off(), &P.qA, 0, (bA * NGRP + kc) * 192 + 64, 0, bars + c0.full() * 8);
        tma_3d(sm + c0.off() + 16384, &P.qA, 0, (bA * NGRP + kc) * 192 + 128, 0, bars + c0.full() * 8);
        mbar_arrive(bars + (c0.full() + 1) * 8);
        mbar_arrive(bars + (c0.full() + 2) * 8);
      }
      {
#pragma unroll 1
        for (int i = 0; i < NGS; i++) { mbar_wait(bars, c.empty(), c.phase ^ 1); c.next(); }
        GCur<1> x; x.init(0);
        bool ext_ok = false;
        auto acquire = [&]() {
          if (x.slot >= NGS && !ext_ok) { mbar_wait(bars, B_EVA + 4, 0); ext_ok = true; }
          mbar_wait(bars, x.empty(), x.phase ^ 1);
        };
#pragma unroll 1
        for (int br = 0; br < 2; br++) {
          const CUtensorMap* mw = br ? &P.woB : &P.woA;
          const CUtensorMap* mo = br ? &P.oB : &P.oA;
          if (br == 0) ldWS(&P.woAt, kc * 512, 2 * n_t);
#pragma unroll 1
          for (int i = 0; i < WREG / 3; i++) {
            acquire();
            mbar_expect_tx(bars + x.full() * 8, XBYTES);
            tma_3d(sm + x.off(), mw, 0, kc * 512 + i * 48, 2 * n_t, bars + x.full() * 8);
            x.next();
          }
          if (br == 1) ldWS(&P.woBt, kc * 512, 2 * n_t);
#pragma unroll 1
          for (int s = 0; s < 4; s++) {
            mbar_wait(bars, B_RDY + 5 + br * 4 + s, 0);
#pragma unroll 1
            for (int i = 0; i < 4; i++) {
              acquire();
              mbar_expect_tx(bars + x.full() * 8, XBYTES);
              tma_3d(sm + x.off(), mo, 0, (4 * j + s) * SQ, kc * 8 + 2 * i, bars + x.full() * 8);
              x.next();
            }
          }
        }
#pragma unroll 1
        for (int f = 0; f < 8; f++) {
          mbar_wait(bars, B_RDY + 13 + f, 0);
          const uint4* src = g_part + ((size_t)((((f >> 2) * NB + 4 * j + (f & 3)) * 4 + n_t) * 8 + kc)) * (8 * 96);
          acquire();
          mbar_expect_tx(bars + x.full() * 8, XBYTES);
          bulk_g2s(sm + x.off(), src, XBYTES, bars + x.full() * 8);
          x.next();
        }
      }
    } else if (warp == 2) {
      if (lane < 2) {
        const int nev = lane == 0 ? 16 : 5;
        int e = lane == 0 ? 1 : 0;
        while (e < nev) {
          if (mbar_test(bars + ((lane == 0 ? B_EVG : B_EVA) + e) * 8, 0)) {
            __threadfence();
            if (lane == 0 && e < 4) {
              fence_proxy_async_global();
              mbar_arrive(bars + (B_RDY + (e < UA ? e : e + 1)) * 8);
            } else {
              unsigned* f;
              if (lane == 0) {
                if (e < 8) f = &g_flags.qa_cnt[((4 * j + (e & 3)) * NGRP + kc) * 8];
                else f = &g_flags.part_cnt[(((e < 12 ? 0 : 1) * NB + 4 * j + (e & 3)) * 4 + n_t) * 8];
              } else {
                f = (e == UA) ? &g_flags.oa_cnt[((4 * j + (h & 3)) * NGRP + kc) * 8]
                              : &g_flags.ob_cnt[((4 * j + (e < UA ? e : e - 1)) * NGRP + kc) * 8];
              }
              red_add(f, 1);
            }
            e++;
          } else {
            if (expired(bars)) break;
            __nanosleep(POLL_NS);
          }
        }
      }
    } else if (warp == 3) {
      unsigned ep1 = 0;
      if (lane == 0) {
        const unsigned e = *reinterpret_cast<volatile unsigned*>(&g_flags.epoch);
        ep1 = e + 1;
        __threadfence();
        const unsigned old = atomicAdd(&g_flags.started, 1u);
        if (old == gridDim.x - 1) {
          g_flags.started = 0;
          __threadfence();
          *reinterpret_cast<volatile unsigned*>(&g_flags.epoch) = e + 1;
        }
      }
      ep1 = __shfl_sync(0xffffffffu, ep1, 0);
      const bool mine = (lane == UA) || (lane >= 5 && lane < 21);
      const unsigned* f = &g_flags.qa_cnt[((4 * j + (h & 3)) * NGRP + kc) * 8];
      unsigned target = 4 * ep1;
      if (lane >= 5 && lane < 9) { f = &g_flags.oa_cnt[((4 * j + lane - 5) * NGRP + kc) * 8]; target = ep1; }
      else if (lane >= 9 && lane < 13) { f = &g_flags.ob_cnt[((4 * j + lane - 9) * NGRP + kc) * 8]; target = 4 * ep1; }
      else if (lane >= 13 && lane < 21) { f = &g_flags.part_cnt[((((lane - 13) >> 2) * NB + 4 * j + ((lane - 13) & 3)) * 4 + n_t) * 8]; target = 8 * ep1; }
      bool done = !mine;
      while (true) {
        if (!done && (int)(ld_acquire(f) - target) >= 0) {
          fence_proxy_async_global();
          mbar_arrive(bars + (B_RDY + lane) * 8);
          done = true;
        }
        if (__all_sync(0xffffffffu, done)) break;
        if (__any_sync(0xffffffffu, expired(bars))) break;
        __nanosleep(POLL_NS);
      }
    }
  } else {
    asm volatile("setmaxnreg.inc.sync.aligned.u32 160;");
    GCur<0> gc; gc.init(0);
    uint32_t qs = sm + SM_QS;
    int qe0 = 0;
    if (wg != 0) {
      gemm_qb(sm, bars, gc);
      gemm_qa(sm, bars, gc);
      mbar_wait(bars, B_EVA + UA - 1, 0);
#pragma unroll 1
      for (int i = 0; i < QPAD; i++) {
        mbar_wait(bars, gc.full(), gc.phase);
        if (lane == 0) mbar_arrive(bars + gc.empty() * 8);
        gc.next();
      }
      qs = sm + gc.off() + (wg - 1) * 16384;
      qe0 = gc.empty();
#pragma unroll 1
      for (int i = 0; i < 3; i++) { mbar_wait(bars, gc.full(), gc.phase); gc.next(); }
    }
    {
      KCur cur; cur.init(wg == 0 ? 0 : KV_POS_A);
      const int u1 = wg == 0 ? 5 : UA + 1;
#pragma unroll 1
      for (int u = (wg == 0 ? 0 : UA); u < u1; u++) {
        if (tid == 0) TSTAMP(1 + 2 * u);
        attn_unit(sm, bars, cur, u, qs);
        if (tid == 0) TSTAMP(2 + 2 * u);
      }
    }
    if (wg != 0) {
      named_bar(5, 256);
      if (lane == 0) for (int i = 0; i < 3; i++) mbar_arrive(bars + (qe0 + i) * 8);
      gemm_op(sm, bars, P.out);
      if (tid == 128) TSTAMP(48);
    }
  }
}

typedef CUresult (*EncodeFn)(CUtensorMap*, CUtensorMapDataType, cuuint32_t, void*, const cuuint64_t*, const cuuint64_t*,
                             const cuuint32_t*, const cuuint32_t*, CUtensorMapInterleave, CUtensorMapSwizzle,
                             CUtensorMapL2promotion, CUtensorMapFloatOOBfill);

static bool make_map(EncodeFn fn, CUtensorMap* m, const void* base, uint64_t rows, uint64_t row_elems, uint32_t box_rows) {
  cuuint64_t dims[3] = {64, rows, row_elems / 64};
  cuuint64_t strides[2] = {row_elems * 2, 128};
  cuuint32_t box[3] = {64, box_rows, 2};
  cuuint32_t estr[3] = {1, 1, 1};
  CUresult r = fn(m, CU_TENSOR_MAP_DATA_TYPE_BFLOAT16, 3, const_cast<void*>(base), dims, strides, box, estr,
                  CU_TENSOR_MAP_INTERLEAVE_NONE, CU_TENSOR_MAP_SWIZZLE_128B, CU_TENSOR_MAP_L2_PROMOTION_L2_256B,
                  CU_TENSOR_MAP_FLOAT_OOB_FILL_NONE);
  if (r != CUDA_SUCCESS) fprintf(stderr, "cuTensorMapEncodeTiled failed: %d\n", (int)r);
  return r == CUDA_SUCCESS;
}

}

extern "C" void kernel_launch(void* const* d_in, const int* in_sizes, int n_in, void* d_out, int out_size) {
  using namespace mk;
  static Params P;
  static bool init = false;
  static void* cached[11] = {0};
  bool same = init;
  for (int i = 0; i < 10; i++) same = same && (cached[i] == d_in[i]);
  same = same && (cached[10] == d_out);
  if (!same) {
    void* fnp = nullptr;
    cudaDriverEntryPointQueryResult qr;
    cudaGetDriverEntryPoint("cuTensorMapEncodeTiled", &fnp, cudaEnableDefault, &qr);
    EncodeFn fn = (EncodeFn)fnp;
    void *qa, *qb, *oa, *ob;
    cudaGetSymbolAddress(&qa, g_QA); cudaGetSymbolAddress(&qb, g_QB);
    cudaGetSymbolAddress(&oa, g_OA); cudaGetSymbolAddress(&ob, g_OB);
    make_map(fn, &P.xA, d_in[0], 768, 512, 48);
    make_map(fn, &P.kA, d_in[1], (uint64_t)NB * NGRP * SK, 128, 64);
    make_map(fn, &P.vA, d_in[2], (uint64_t)NB * NGRP * SK, 128, 64);
    make_map(fn, &P.wqA, d_in[3], 512, 4096, 48);
    make_map(fn, &P.wqAt, d_in[3], 512, 4096, (32 - WREG) * 16);
    make_map(fn, &P.woA, d_in[4], 4096, 512, 48);
    make_map(fn, &P.woAt, d_in[4], 4096, 512, (32 - WREG) * 16);
    make_map(fn, &P.xB, d_in[5], 768, 512, 48);
    make_map(fn, &P.kB, d_in[6], (uint64_t)NB * NH * SK, 128, 64);
    make_map(fn, &P.vB, d_in[7], (uint64_t)NB * NH * SK, 128, 64);
    make_map(fn, &P.wqB, d_in[8], 512, 4096, 48);
    make_map(fn, &P.wqBt, d_in[8], 512, 4096, (32 - WREG) * 16);
    make_map(fn, &P.woB, d_in[9], 4096, 512, 48);
    make_map(fn, &P.woBt, d_in[9], 4096, 512, (32 - WREG) * 16);
    make_map(fn, &P.qA, qa, (uint64_t)NB * NGRP * 192, 128, 64);
    make_map(fn, &P.qB, qb, (uint64_t)NB * NH * SQ + 16, 128, 64);
    make_map(fn, &P.oA, oa, 768, 4096, 48);
    make_map(fn, &P.oB, ob, 768, 4096, 48);
    P.out = (bf16*)d_out;
    cudaFuncSetAttribute(fused_kernel, cudaFuncAttributeMaxDynamicSharedMemorySize, SM_TOTAL);
    for (int i = 0; i < 10; i++) cached[i] = d_in[i];
    cached[10] = d_out;
    init = true;
  }
  fused_kernel<<<NCTA, NTHREADS, SM_TOTAL>>>(P);
}
```

```cpp
#include <cuda_runtime.h>
#include <cuda_bf16.h>
#include <cuda.h>
#include <stdint.h>
#include <stdio.h>
#include <stdlib.h>

namespace mk {

typedef __nv_bfloat16 bf16;

constexpr int NB = 16, SQ = 48, NH = 32, NGRP = 8, SK = 512, DH = 128;
constexpr int SLOT = 16384;
#define NKVS 8
#define NGS 5
#define KVGO -1
#define PF0 0
#define PF0_DELAY 500
#define OPA_NARROW 1
#define WPF 0
#define ROT(c) 0
#define POLL_NS 64
#define WAIT_HINT_NS 100000u
constexpr int XBYTES = 12288;
constexpr int WREG = 27;
constexpr int SM_QS = 0;
constexpr int SM_KV = 16384;
constexpr int SM_G = SM_KV + NKVS * SLOT;
constexpr int SM_WS = SM_G + NGS * XBYTES;
constexpr int SM_BAR = SM_WS + (32 - WREG) * 4096;
constexpr int SM_TOTAL = SM_BAR + 1024 + 1024;
constexpr int NEXT = (NKVS * SLOT) / XBYTES;
constexpr int NWIDE = NGS + NEXT;
constexpr int SM_EXT = SM_G - NEXT * XBYTES;
static_assert(NEXT >= WREG / 3, "the first weight tile is loaded into the extra slots");
constexpr int QP_ENTRIES = 8 * 4 + 2 * (WREG / 3);
#define UA_POS 3
constexpr int UA = UA_POS;
constexpr int KV_POS_A = 16 + 17 * (UA - 1);
constexpr int QPAD = (QP_ENTRIES % NGS + 3 > NGS) ? NGS - QP_ENTRIES % NGS : 0;
constexpr int NCTA = 128;
constexpr int NTHREADS = 512;

constexpr int B_KVF = 0;
constexpr int B_KVE = B_KVF + NKVS;
constexpr int B_GF = B_KVE + NKVS;
constexpr int B_GE = B_GF + NGS;
constexpr int B_EVG = B_GE + NGS;
constexpr int B_EVA = B_EVG + 16;
constexpr int B_WSF = B_EVA + 5;
constexpr int B_WSE = B_WSF + 1;
constexpr int B_WQF = B_WSE + 1;
constexpr int B_WQE = B_WQF + WREG / 3;
constexpr int B_XF = B_WQE + 1;
constexpr int B_XE = B_XF + NWIDE;
constexpr int B_RDY = B_XE + NWIDE;
constexpr int B_Q0 = B_RDY + 21;
constexpr int B_END = B_Q0 + 1;
static_assert(B_END * 8 + 16 <= 1024 && B_END <= 512, "barrier region");
static_assert(SM_TOTAL <= 232448, "smem");

struct alignas(64) Params {
  CUtensorMap kA, vA, kB, vB, qA, qB;
  CUtensorMap xA, xB;
  CUtensorMap oA, oB;
  CUtensorMap wqA, wqB, woA, woB;
  CUtensorMap wqAt, wqBt, woAt, woBt;
  bf16* out;
};

__device__ bf16 g_QA[NB * NGRP * 192 * DH];
__device__ bf16 g_QB[NB * NH * SQ * DH + 16 * DH];
__device__ uint4 g_part[2 * NB * 4 * 8 * 8 * 96];
struct Flags {
  unsigned epoch;
  unsigned pad0[31];
  unsigned started;
  unsigned pad1[31];
  unsigned qa_cnt[NB * NGRP * 8];
  unsigned oa_cnt[NB * NGRP * 8];
  unsigned ob_cnt[NB * NGRP * 8];
  unsigned part_cnt[2 * NB * 4 * 8];
};
__device__ Flags g_flags;
__constant__ uint32_t c_zero;

#define TSTAMP(idx) do {} while (0)

__device__ __forceinline__ uint32_t smem_u32(const void* p) { return (uint32_t)__cvta_generic_to_shared(p); }
__device__ __forceinline__ void mbar_init(uint32_t bar, uint32_t cnt) {
  asm volatile("mbarrier.init.shared::cta.b64 [%0], %1;" ::"r"(bar), "r"(cnt) : "memory");
}
__device__ __forceinline__ void mbar_expect_tx(uint32_t bar, uint32_t bytes) {
  asm volatile("mbarrier.arrive.expect_tx.shared::cta.b64 _, [%0], %1;" ::"r"(bar), "r"(bytes) : "memory");
}
__device__ __forceinline__ void mbar_arrive(uint32_t bar) {
  asm volatile("mbarrier.arrive.shared::cta.b64 _, [%0];" ::"r"(bar) : "memory");
}
__device__ __forceinline__ void mbar_arrive_n(uint32_t bar, uint32_t n) {
  asm volatile("mbarrier.arrive.shared::cta.b64 _, [%0], %1;" ::"r"(bar), "r"(n) : "memory");
}
__device__ __forceinline__ bool mbar_try(uint32_t bar, uint32_t parity) {
  uint32_t ok;
  asm volatile("{\n.reg .pred p;\nmbarrier.try_wait.parity.shared::cta.b64 p, [%1], %2, %3;\nselp.u32 %0, 1, 0, p;\n}"
               : "=r"(ok) : "r"(bar), "r"(parity), "r"(WAIT_HINT_NS) : "memory");
  return ok != 0;
}
__device__ __forceinline__ bool mbar_test(uint32_t bar, uint32_t parity) {
  uint32_t ok;
  asm volatile("{\n.reg .pred p;\nmbarrier.test_wait.parity.shared::cta.b64 p, [%1], %2;\nselp.u32 %0, 1, 0, p;\n}"
               : "=r"(ok) : "r"(bar), "r"(parity) : "memory");
  return ok != 0;
}
__device__ __forceinline__ bool expired(uint32_t bars) {
  uint32_t t0, t1;
  asm volatile("ld.volatile.shared.u32 %0, [%1];" : "=r"(t0) : "r"(bars + B_END * 8));
  asm volatile("mov.u32 %0, %%clock;" : "=r"(t1));
  return (t1 - t0) > 1900000000u;
}
__device__ __forceinline__ int opaque_tid() {
  int t;
  asm volatile("mov.u32 %0, %%tid.x;" : "=r"(t));
  return t;
}
__device__ __forceinline__ int opaque_cta() {
  int t;
  asm volatile("mov.u32 %0, %%ctaid.x;" : "=r"(t));
  return t;
}
__device__ __forceinline__ void mbar_wait(uint32_t bars, int idx, uint32_t parity) {
  while (!mbar_try(bars + idx * 8, parity)) {
    if (expired(bars)) break;
  }
}
__device__ __forceinline__ unsigned ld_acquire(const unsigned* p) {
  unsigned v;
  asm volatile("ld.acquire.gpu.global.u32 %0, [%1];" : "=r"(v) : "l"(p) : "memory");
  return v;
}
__device__ __forceinline__ void red_add(unsigned* p, unsigned v) {
  asm volatile("red.relaxed.gpu.global.add.u32 [%0], %1;" ::"l"(p), "r"(v) : "memory");
}
__device__ __forceinline__ void fence_proxy_async() { asm volatile("fence.proxy.async.shared::cta;" ::: "memory"); }
__device__ __forceinline__ void fence_proxy_async_global() { asm volatile("fence.proxy.async.global;" ::: "memory"); }
__device__ __forceinline__ void tma_3d(uint32_t dst, const CUtensorMap* map, int c0, int c1, int c2, uint32_t bar) {
  asm volatile(
      "cp.async.bulk.tensor.3d.shared::cluster.global.mbarrier::complete_tx::bytes [%0], [%1, {%3, %4, %5}], [%2];" ::"r"(dst),
      "l"(map), "r"(bar), "r"(c0), "r"(c1), "r"(c2)
      : "memory");
}
__device__ __forceinline__ void tma_3d_hint(uint32_t dst, const CUtensorMap* map, int c0, int c1, int c2, uint32_t bar, uint64_t pol) {
  asm volatile(
      "cp.async.bulk.tensor.3d.shared::cluster.global.mbarrier::complete_tx::bytes.L2::cache_hint [%0], [%1, {%3, %4, %5}], [%2], %6;" ::"r"(dst),
      "l"(map), "r"(bar), "r"(c0), "r"(c1), "r"(c2), "l"(pol)
      : "memory");
}
__device__ __forceinline__ void tma_prefetch_3d(const CUtensorMap* map, int c0, int c1, int c2) {
  asm volatile("cp.async.bulk.prefetch.tensor.3d.L2.global [%0, {%1, %2, %3}];" ::"l"(map), "r"(c0), "r"(c1), "r"(c2) : "memory");
}
__device__ __forceinline__ uint64_t policy_evict_first() {
  uint64_t pol;
  asm volatile("createpolicy.fractional.L2::evict_first.b64 %0, 1.0;" : "=l"(pol));
  return pol;
}
__device__ __forceinline__ void bulk_g2s(uint32_t dst, const void* src, uint32_t bytes, uint32_t bar) {
  asm volatile("cp.async.bulk.shared::cluster.global.mbarrier::complete_tx::bytes [%0], [%1], %2, [%3];" ::"r"(dst), "l"(src),
               "r"(bytes), "r"(bar)
               : "memory");
}
__device__ __forceinline__ void prefetch_tmap(const CUtensorMap* map) {
  asm volatile("prefetch.tensormap [%0];" ::"l"(map) : "memory");
}
__device__ __forceinline__ void ldsm_x4_t(uint32_t (&r)[4], uint32_t addr) {
  asm volatile("ldmatrix.sync.aligned.m8n8.x4.trans.shared.b16 {%0,%1,%2,%3}, [%4];"
               : "=r"(r[0]), "=r"(r[1]), "=r"(r[2]), "=r"(r[3]) : "r"(addr) : "memory");
}
__device__ __forceinline__ void stsm_x4(uint32_t addr, uint32_t r0, uint32_t r1, uint32_t r2, uint32_t r3) {
  asm volatile("stmatrix.sync.aligned.m8n8.x4.shared.b16 [%0], {%1,%2,%3,%4};" ::"r"(addr), "r"(r0), "r"(r1), "r"(r2), "r"(r3)
               : "memory");
}
__device__ __forceinline__ uint4 lds128(uint32_t addr) {
  uint4 v;
  asm volatile("ld.shared.v4.u32 {%0,%1,%2,%3}, [%4];" : "=r"(v.x), "=r"(v.y), "=r"(v.z), "=r"(v.w) : "r"(addr) : "memory");
  return v;
}
__device__ __forceinline__ void sts128(uint32_t addr, uint4 v) {
  asm volatile("st.shared.v4.u32 [%0], {%1,%2,%3,%4};" ::"r"(addr), "r"(v.x), "r"(v.y), "r"(v.z), "r"(v.w) : "memory");
}
__device__ __forceinline__ uint32_t dep_on(uint32_t addr, uint32_t loaded) { return addr + (loaded & c_zero); }
__device__ __forceinline__ void named_bar(int id, int n) { asm volatile("bar.sync %0, %1;" ::"r"(id), "r"(n) : "memory"); }
__device__ __forceinline__ void wg_fence() { asm volatile("wgmma.fence.sync.aligned;" ::: "memory"); }
__device__ __forceinline__ void wg_commit() { asm volatile("wgmma.commit_group.sync.aligned;" ::: "memory"); }
template <int N>
__device__ __forceinline__ void wg_wait() { asm volatile("wgmma.wait_group.sync.aligned %0;" ::"n"(N) : "memory"); }
template <int N>
__device__ __forceinline__ void fence_regs(float (&a)[N]) {
#pragma unroll
  for (int i = 0; i < N; i++) asm volatile("" : "+f"(a[i])::"memory");
}
__device__ __forceinline__ uint64_t make_desc(uint32_t addr, uint32_t lbo, uint32_t sbo) {
  return (uint64_t)((addr & 0x3FFFF) >> 4) | ((uint64_t)(lbo >> 4) << 16) | ((uint64_t)(sbo >> 4) << 32) | (1ull << 62);
}
__device__ __forceinline__ uint32_t pack_bf16(float lo, float hi) {
  uint32_t r;
  asm("cvt.rn.bf16x2.f32 %0, %1, %2;" : "=r"(r) : "f"(hi), "f"(lo));
  return r;
}
__device__ __forceinline__ float ex2(float x) {
  float y;
  asm("ex2.approx.ftz.f32 %0, %1;" : "=f"(y) : "f"(x));
  return y;
}
__device__ __forceinline__ float rcp(float x) {
  float y;
  asm("rcp.approx.ftz.f32 %0, %1;" : "=f"(y) : "f"(x));
  return y;
}
__device__ __forceinline__ uint32_t movmatrix_t(uint32_t x) {
  uint32_t y;
  asm volatile("movmatrix.sync.aligned.m8n8.trans.b16 %0, %1;" : "=r"(y) : "r"(x));
  return y;
}

#define ACC8(d, o) "+f"(d[o]), "+f"(d[o + 1]), "+f"(d[o + 2]), "+f"(d[o + 3]), "+f"(d[o + 4]), "+f"(d[o + 5]), "+f"(d[o + 6]), "+f"(d[o + 7])
__device__ __forceinline__ void wgmma_n64_ss(float (&d)[32], uint64_t da, uint64_t db, int scale_d) {
  asm volatile(
      "{\n.reg .pred p;\nsetp.ne.b32 p, %34, 0;\n"
      "wgmma.mma_async.sync.aligned.m64n64k16.f32.bf16.bf16 "
      "{%0,%1,%2,%3,%4,%5,%6,%7,%8,%9,%10,%11,%12,%13,%14,%15,%16,%17,%18,%19,%20,%21,%22,%23,%24,%25,%26,%27,%28,%29,%30,%31},"
      "%32, %33, p, 1, 1, 0, 0;\n}"
      : ACC8(d, 0), ACC8(d, 8), ACC8(d, 16), ACC8(d, 24)
      : "l"(da), "l"(db), "r"(scale_d));
}
__device__ __forceinline__ void wgmma_n128_t(float (&d)[64], const uint32_t (&a)[4], uint64_t desc, int scale_d) {
  asm volatile(
      "{\n.reg .pred p;\nsetp.ne.b32 p, %69, 0;\n"
      "wgmma.mma_async.sync.aligned.m64n128k16.f32.bf16.bf16 "
      "{%0,%1,%2,%3,%4,%5,%6,%7,%8,%9,%10,%11,%12,%13,%14,%15,%16,%17,%18,%19,%20,%21,%22,%23,%24,%25,%26,%27,%28,%29,%30,%31,"
      "%32,%33,%34,%35,%36,%37,%38,%39,%40,%41,%42,%43,%44,%45,%46,%47,%48,%49,%50,%51,%52,%53,%54,%55,%56,%57,%58,%59,%60,%61,%62,%63},"
      "{%64,%65,%66,%67}, %68, p, 1, 1, 1;\n}"
      : ACC8(d, 0), ACC8(d, 8), ACC8(d, 16), ACC8(d, 24), ACC8(d, 32), ACC8(d, 40), ACC8(d, 48), ACC8(d, 56)
      : "r"(a[0]), "r"(a[1]), "r"(a[2]), "r"(a[3]), "l"(desc), "r"(scale_d));
}
__device__ __forceinline__ void wgmma_n48(float (&d)[24], const uint32_t (&a)[4], uint64_t desc, int scale_d) {
  asm volatile(
      "{\n.reg .pred p;\nsetp.ne.b32 p, %29, 0;\n"
      "wgmma.mma_async.sync.aligned.m64n48k16.f32.bf16.bf16 "
      "{%0,%1,%2,%3,%4,%5,%6,%7,%8,%9,%10,%11,%12,%13,%14,%15,%16,%17,%18,%19,%20,%21,%22,%23},"
      "{%24,%25,%26,%27}, %28, p, 1, 1, 0;\n}"
      : ACC8(d, 0), ACC8(d, 8), ACC8(d, 16)
      : "r"(a[0]), "r"(a[1]), "r"(a[2]), "r"(a[3]), "l"(desc), "r"(scale_d));
}
__device__ __forceinline__ void wgmma_n48_ss(float (&d)[24], uint64_t descA, uint64_t descB) {
  asm volatile(
      "{\n.reg .pred p;\nsetp.ne.b32 p, 1, 0;\n"
      "wgmma.mma_async.sync.aligned.m64n48k16.f32.bf16.bf16 "
      "{%0,%1,%2,%3,%4,%5,%6,%7,%8,%9,%10,%11,%12,%13,%14,%15,%16,%17,%18,%19,%20,%21,%22,%23},"
      "%24, %25, p, 1, 1, 1, 0;\n}"
      : ACC8(d, 0), ACC8(d, 8), ACC8(d, 16)
      : "l"(descA), "l"(descB));
}

struct KCur {
  int slot;
  uint32_t phase;
  __device__ __forceinline__ void init(int count) { slot = count % NKVS; phase = (count / NKVS) & 1; }
  __device__ __forceinline__ void next() { if (++slot == NKVS) { slot = 0; phase ^= 1; } }
};
template <int MODE>
struct GCur {
  int slot;
  uint32_t phase;
  static constexpr int N = MODE == 0 ? NGS : (MODE == 1 ? NWIDE : WREG / 3);
  __device__ __forceinline__ void init(int count) { slot = count % N; phase = (count / N) & 1; }
  __device__ __forceinline__ void next() { if (++slot == N) { slot = 0; phase ^= 1; } }
  __device__ __forceinline__ uint32_t off() const {
    if (MODE == 0) return SM_G + slot * XBYTES;
    if (MODE == 1) return SM_EXT + (slot < NGS ? slot + NEXT : slot - NGS) * XBYTES;
    return SM_EXT + slot * XBYTES;
  }
  __device__ __forceinline__ int full() const { return (MODE == 0 ? B_GF : (MODE == 1 ? B_XF : B_WQF)) + slot; }
  __device__ __forceinline__ int empty() const { return MODE == 2 ? B_WQE : (MODE == 0 ? B_GE : B_XE) + slot; }
};

constexpr float SM_C = 0.08838834764831845f * 1.4426950408889634f;
constexpr float RESCALE_T = 8.0f;

__device__ __forceinline__ void softmax_step(const float (&s)[32], uint32_t (&pf)[4][4], float (&o)[64], float& m0, float& m1,
                                             float& l0, float& l1, bool first) {
  float mx0 = fmaxf(s[0], s[1]), mx1 = fmaxf(s[2], s[3]);
#pragma unroll
  for (int j = 1; j < 8; j++) {
    mx0 = fmaxf(mx0, fmaxf(s[4 * j], s[4 * j + 1]));
    mx1 = fmaxf(mx1, fmaxf(s[4 * j + 2], s[4 * j + 3]));
  }
  mx0 = fmaxf(mx0, __shfl_xor_sync(0xffffffffu, mx0, 1));
  mx1 = fmaxf(mx1, __shfl_xor_sync(0xffffffffu, mx1, 1));
  mx0 = fmaxf(mx0, __shfl_xor_sync(0xffffffffu, mx0, 2));
  mx1 = fmaxf(mx1, __shfl_xor_sync(0xffffffffu, mx1, 2));
  const bool grow = !((mx0 - m0) * SM_C <= RESCALE_T) || !((mx1 - m1) * SM_C <= RESCALE_T);
  if (__any_sync(0xffffffffu, grow)) {
    const float mn0 = fmaxf(m0, mx0), mn1 = fmaxf(m1, mx1);
    const float a0 = ex2((m0 - mn0) * SM_C), a1 = ex2((m1 - mn1) * SM_C);
    m0 = mn0; m1 = mn1;
    l0 *= a0; l1 *= a1;
    if (!first) {
#pragma unroll
      for (int j = 0; j < 16; j++) {
        o[4 * j] *= a0; o[4 * j + 1] *= a0; o[4 * j + 2] *= a1; o[4 * j + 3] *= a1;
      }
    }
  }
  const float mc0 = m0 * SM_C, mc1 = m1 * SM_C;
#pragma unroll
  for (int j = 0; j < 8; j++) {
    const float p0 = ex2(fmaf(s[4 * j], SM_C, -mc0)), p1 = ex2(fmaf(s[4 * j + 1], SM_C, -mc0));
    const float p2 = ex2(fmaf(s[4 * j + 2], SM_C, -mc1)), p3 = ex2(fmaf(s[4 * j + 3], SM_C, -mc1));
    l0 += p0 + p1; l1 += p2 + p3;
    pf[j >> 1][(j & 1) * 2 + 0] = pack_bf16(p0, p1);
    pf[j >> 1][(j & 1) * 2 + 1] = pack_bf16(p2, p3);
  }
}

__device__ __forceinline__ void attn_unit(uint32_t sm, uint32_t bars, KCur& cur, int u, uint32_t qs) {
  const int tid_ = opaque_tid();
  const bool leader = (tid_ & 31) == 0;
  const bool isA = (u == UA);
  const uint32_t narr = isA ? 1 : 3;
  const bool active = isA || (tid_ >> 5) < 3;
  if (u == 0) {
    mbar_wait(bars, B_Q0, 0);
  } else {
    mbar_wait(bars, B_KVF + cur.slot, cur.phase);
    uint32_t rel = bars + (B_KVE + cur.slot) * 8;
    if (tid_ < 128) {
      named_bar(1, 128);
      const uint32_t src = sm + SM_KV + cur.slot * SLOT + tid_ * 16, dst = qs + tid_ * 16;
      uint32_t x = 0;
#pragma unroll
      for (int i = 0; i < 8; i++) {
        const uint4 v = lds128(src + i * 2048);
        sts128(dst + i * 2048, v);
        x ^= v.x;
      }
      rel = dep_on(rel, x);
      fence_proxy_async();
      named_bar(1, 128);
    }
    if (leader) mbar_arrive_n(rel, narr);
    cur.next();
  }
  float o[64];
  float s[32];
  float m0 = -INFINITY, m1 = -INFINITY, l0 = 0.f, l1 = 0.f;
  mbar_wait(bars, B_KVF + cur.slot, cur.phase);
  wg_fence();
#pragma unroll
  for (int ks = 0; ks < 8; ks++)
    wgmma_n64_ss(s, make_desc(qs + (ks >> 2) * 8192 + (ks & 3) * 32, 16, 1024),
                 make_desc(sm + SM_KV + cur.slot * SLOT + (ks >> 2) * 8192 + (ks & 3) * 32, 16, 1024), ks > 0);
  wg_commit();
  wg_wait<0>();
  fence_regs(s);
  if (leader) mbar_arrive_n(bars + (B_KVE + cur.slot) * 8, narr);
  cur.next();
#pragma unroll 1
  for (int t = 0; t < 8; t++) {
    uint32_t pf[4][4];
    if (active) softmax_step(s, pf, o, m0, m1, l0, l1, t == 0);
    else {
#pragma unroll
      for (int k = 0; k < 4; k++) { pf[k][0] = 0; pf[k][1] = 0; pf[k][2] = 0; pf[k][3] = 0; }
    }
    const int vs = cur.slot; const uint32_t vp = cur.phase; cur.next();
    mbar_wait(bars, B_KVF + vs, vp);
    wg_fence();
#pragma unroll
    for (int kk = 0; kk < 4; kk++)
      wgmma_n128_t(o, pf[kk], make_desc(sm + SM_KV + vs * SLOT + kk * 2048, 8192, 1024), (t > 0) || (kk > 0));
    wg_commit();
    if (t < 7) {
      const int ks_ = cur.slot;
      mbar_wait(bars, B_KVF + ks_, cur.phase);
      cur.next();
      wg_fence();
#pragma unroll
      for (int ks = 0; ks < 8; ks++)
        wgmma_n64_ss(s, make_desc(qs + (ks >> 2) * 8192 + (ks & 3) * 32, 16, 1024),
                     make_desc(sm + SM_KV + ks_ * SLOT + (ks >> 2) * 8192 + (ks & 3) * 32, 16, 1024), ks > 0);
      wg_commit();
      wg_wait<1>();
      if (leader) mbar_arrive_n(bars + (B_KVE + vs) * 8, narr);
      wg_wait<0>();
      if (leader) mbar_arrive_n(bars + (B_KVE + ks_) * 8, narr);
    } else {
      wg_wait<0>();
      if (leader) mbar_arrive_n(bars + (B_KVE + vs) * 8, narr);
    }
    fence_regs(s); fence_regs(o);
  }
  if (active) {
    l0 += __shfl_xor_sync(0xffffffffu, l0, 1); l1 += __shfl_xor_sync(0xffffffffu, l1, 1);
    l0 += __shfl_xor_sync(0xffffffffu, l0, 2); l1 += __shfl_xor_sync(0xffffffffu, l1, 2);
    const float i0 = rcp(l0), i1 = rcp(l1);
    const int tid = opaque_tid(), cta = opaque_cta();
    const int lane = tid & 31, w4 = (tid >> 5) & 3;
    named_bar(2 + (tid >> 7), isA ? 128 : 96);
    const uint32_t stg = qs + w4 * 4096;
    {
      const int mi = lane >> 3, row = (mi & 1) * 8 + (lane & 7);
#pragma unroll
      for (int jp = 0; jp < 8; jp++) {
        const int chunk = 2 * jp + (mi >> 1);
        stsm_x4(stg + row * 256 + ((chunk ^ (row & 7)) << 4), pack_bf16(o[8 * jp] * i0, o[8 * jp + 1] * i0),
                pack_bf16(o[8 * jp + 2] * i1, o[8 * jp + 3] * i1), pack_bf16(o[8 * jp + 4] * i0, o[8 * jp + 5] * i0),
                pack_bf16(o[8 * jp + 6] * i1, o[8 * jp + 7] * i1));
      }
    }
    __syncwarp();
    const int h = cta >> 2, jg = cta & 3;
    const int r0 = (tid >> 5) * 16;
    bf16* orow = isA ? g_QA + (size_t)(((4 * jg + (h & 3)) * NGRP + (h >> 2)) * 192 + r0) * DH
                     : g_QB + (size_t)(((4 * jg + (u < UA ? u : u - 1)) * NH + h) * SQ + r0) * DH;
#pragma unroll 2
    for (int i = 0; i < 8; i++) {
      const int row = 2 * i + (lane >> 4), chunk = lane & 15;
      const uint4 v = lds128(stg + row * 256 + ((chunk ^ (row & 7)) << 4));
      *reinterpret_cast<uint4*>(orow + row * DH + chunk * 8) = v;
    }
  }
  __syncwarp();
  if ((opaque_tid() & 31) == 0) mbar_arrive(bars + (B_EVA + u) * 8);
}

template <int MODE>
__device__ __forceinline__ void load_w(uint32_t (&wf)[WREG][4], uint32_t sm, uint32_t bars, GCur<MODE>& cur) {
  const int tid = opaque_tid();
  const int lane = tid & 31, warp = (tid >> 5) & 3, half = (tid >> 7) - 1;
  const int mi = lane >> 3, rr = lane & 7;
  const int chunk = warp * 2 + (mi & 1);
  const uint32_t off = sm + half * 6144 + ((mi >> 1) * 8 + rr) * 128 + ((chunk ^ rr) << 4);
  uint32_t all = 0;
#pragma unroll
  for (int c = 0; c < WREG / 3; c++) {
    mbar_wait(bars, cur.full(), cur.phase);
    const uint32_t base = off + cur.off();
#pragma unroll
    for (int ks = 0; ks < 3; ks++) ldsm_x4_t(wf[c * 3 + ks], base + ks * 2048);
    const uint32_t x = wf[c * 3][0] ^ wf[c * 3 + 1][0] ^ wf[c * 3 + 2][0];
    if (MODE == 2) {
      all ^= x;
    } else {
      const uint32_t rel = dep_on(bars + cur.empty() * 8, x);
      __syncwarp();
      if (lane == 0) mbar_arrive(rel);
    }
    cur.next();
  }
  if (MODE == 2) {
    const uint32_t rel = dep_on(bars + B_WQE * 8, all);
    __syncwarp();
    if (lane == 0) mbar_arrive(rel);
  }
}

template <int MODE>
__device__ __forceinline__ void brick(float (&acc)[24], const uint32_t (&wf)[WREG][4], uint32_t sm, uint32_t bars, GCur<MODE>& cur) {
  int prev_empty = 0;
  const int tid = opaque_tid();
  const bool leader = (tid & 31) == 0;
  const uint32_t ws = sm + SM_WS + ((tid >> 7) - 1) * ((32 - WREG) * 2048);
#pragma unroll
  for (int i = 0; i < 4; i++) {
    mbar_wait(bars, cur.full(), cur.phase);
    const uint32_t base = sm + cur.off();
    wg_fence();
#pragma unroll
    for (int ks = 0; ks < 8; ks++) {
      const uint64_t db = make_desc(base + (ks >> 2) * 6144 + (ks & 3) * 32, 16, 1024);
      if (i * 8 + ks < WREG) wgmma_n48(acc, wf[i * 8 + ks], db, (i > 0) || (ks > 0));
      else wgmma_n48_ss(acc, make_desc(ws + (i * 8 + ks - WREG) * 2048, 8192, 1024), db);
    }
    wg_commit();
    if (i > 0) {
      wg_wait<1>();
      if (leader) mbar_arrive(bars + prev_empty * 8);
    }
    prev_empty = cur.empty();
    cur.next();
  }
  wg_wait<0>();
  fence_regs(acc);
  if (leader) mbar_arrive(bars + prev_empty * 8);
}

__device__ __forceinline__ void epi_q(const float (&acc)[24], int br, int s, uint32_t sm) {
  const int tid = opaque_tid(), cta = opaque_cta();
  const int lane = tid & 31, w8 = (tid >> 5) - 4;
  const int h = cta >> 2, b = 4 * (cta & 3) + s;
  if (br == 1 && s == 0) {
    const uint32_t base = sm + SM_QS + (w8 >> 2) * 8192 + (lane >> 2) * 128 + (lane & 3) * 4;
    const int sw = lane >> 2, ch = (w8 & 3) * 2;
#pragma unroll
    for (int jb = 0; jb < 6; jb++) {
      const uint32_t lo = movmatrix_t(pack_bf16(acc[4 * jb + 0], acc[4 * jb + 1]));
      const uint32_t hi = movmatrix_t(pack_bf16(acc[4 * jb + 2], acc[4 * jb + 3]));
      asm volatile("st.shared.u32 [%0], %1;" ::"r"(base + jb * 1024 + ((ch ^ sw) << 4)), "r"(lo) : "memory");
      asm volatile("st.shared.u32 [%0], %1;" ::"r"(base + jb * 1024 + (((ch + 1) ^ sw) << 4)), "r"(hi) : "memory");
    }
    fence_proxy_async();
    return;
  }
  bf16* dst = br ? g_QB + (size_t)((b * NH + h) * SQ) * DH : g_QA + (size_t)((b * NGRP + (h >> 2)) * 192 + (h & 3) * SQ) * DH;
  bf16* p = dst + w8 * 16 + (lane >> 2) * 128 + (lane & 3) * 2;
#pragma unroll
  for (int jb = 0; jb < 6; jb++) {
    const uint32_t lo = movmatrix_t(pack_bf16(acc[4 * jb + 0], acc[4 * jb + 1]));
    const uint32_t hi = movmatrix_t(pack_bf16(acc[4 * jb + 2], acc[4 * jb + 3]));
    *reinterpret_cast<uint32_t*>(p + jb * 8 * 128) = lo;
    *reinterpret_cast<uint32_t*>(p + jb * 8 * 128 + 8) = hi;
  }
}
__device__ __forceinline__ void epi_part(const float (&acc)[24], int br, int s) {
  const int tid = opaque_tid(), cta = opaque_cta();
  const int lane = tid & 31, w8 = (tid >> 5) - 4;
  const int h = cta >> 2, b = 4 * (cta & 3) + s;
  uint4* dst = g_part + ((size_t)(((br * NB + b) * 4 + (h & 3)) * 8 + w8)) * (8 * 96) + (h >> 2) * 96 + lane;
#pragma unroll
  for (int k = 0; k < 3; k++)
    dst[k * 32] = make_uint4(pack_bf16(acc[8 * k], acc[8 * k + 1]), pack_bf16(acc[8 * k + 2], acc[8 * k + 3]),
                             pack_bf16(acc[8 * k + 4], acc[8 * k + 5]), pack_bf16(acc[8 * k + 6], acc[8 * k + 7]));
}
__device__ __forceinline__ void finalize(uint32_t sm, uint32_t bars, GCur<1>& cur, bf16* out, int br, int q) {
  const int tid = opaque_tid(), cta = opaque_cta();
  const int t256 = tid - 128;
  const int h = cta >> 2;
  bf16* dst = out + (size_t)((4 * (cta & 3) + q) * SQ) * 1024 + br * 512 + (h & 3) * 128 + (h >> 2) * 16;
  mbar_wait(bars, cur.full(), cur.phase);
  const uint32_t b0 = sm + cur.off(); const int e0 = cur.empty(); cur.next();
  if (t256 < 192) {
    const int rp = t256 >> 3, c = (t256 & 7) * 2;
    const int wi = 2 * (rp >> 2) + (c >> 3);
    const uint32_t a0 = b0 + ((wi >> 2) * 32 + (c & 7) * 4 + (rp & 3)) * 16 + (wi & 3) * 4;
    float s00 = 0.f, s01 = 0.f, s10 = 0.f, s11 = 0.f;
#pragma unroll
    for (int p = 0; p < 8; p++) {
      uint32_t x0, x1;
      asm volatile("ld.shared.u32 %0, [%1];" : "=r"(x0) : "r"(a0 + p * 1536));
      asm volatile("ld.shared.u32 %0, [%1+64];" : "=r"(x1) : "r"(a0 + p * 1536));
      s00 += __uint_as_float(x0 << 16); s10 += __uint_as_float(x0 & 0xffff0000u);
      s01 += __uint_as_float(x1 << 16); s11 += __uint_as_float(x1 & 0xffff0000u);
    }
    *reinterpret_cast<uint32_t*>(dst + (2 * rp) * 1024 + c) = pack_bf16(s00, s01);
    *reinterpret_cast<uint32_t*>(dst + (2 * rp + 1) * 1024 + c) = pack_bf16(s10, s11);
  }
  __syncwarp();
  if ((tid & 31) == 0) mbar_arrive(bars + e0 * 8);
}

__device__ __forceinline__ void gemm_q0(uint32_t sm, uint32_t bars, GCur<0>& gc) {
  uint32_t wf[WREG][4];
  {
    GCur<2> wc; wc.init(0);
    load_w<2>(wf, sm, bars, wc);
  }
  mbar_wait(bars, B_WSF, 0);
#pragma unroll 1
  for (int s = 0; s < 2; s++) {
    float acc[24];
    brick<0>(acc, wf, sm, bars, gc);
    const bool leader = (opaque_tid() & 31) == 0;
    if (s == 1 && leader) mbar_arrive(bars + B_WSE * 8);
    epi_q(acc, 1, s, sm);
    __syncwarp();
    if (leader) mbar_arrive(bars + (s == 0 ? B_Q0 : B_EVG + 1) * 8);
    if (threadIdx.x == 128) TSTAMP(17 + s);
  }
}
__device__ __forceinline__ void gemm_q1(uint32_t sm, uint32_t bars, GCur<0>& gc) {
#pragma unroll 1
  for (int br = 0; br < 2; br++) {
    uint32_t wf[WREG][4];
    if (threadIdx.x == 128 && br == 0) TSTAMP(25);
    load_w<0>(wf, sm, bars, gc);
    mbar_wait(bars, B_WSF, (br + 1) & 1);
#pragma unroll 1
    for (int s = 2 * br; s < 4; s++) {
      float acc[24];
      brick<0>(acc, wf, sm, bars, gc);
      const bool leader = (opaque_tid() & 31) == 0;
      if (s == 3 && leader) mbar_arrive(bars + B_WSE * 8);
      epi_q(acc, br, s, sm);
      __syncwarp();
      if (leader) mbar_arrive(bars + (B_EVG + 2 + 2 * br + s) * 8);
      if (threadIdx.x == 128) TSTAMP(br ? 17 + s : 21 + s);
    }
  }
}
__device__ __forceinline__ void gemm_op_narrow(uint32_t sm, uint32_t bars, GCur<0>& gc, bf16* out) {
  GCur<1> xc; xc.init(0);
  {
    uint32_t wf[WREG][4];
    if (threadIdx.x == 128) TSTAMP(32);
    load_w<0>(wf, sm, bars, gc);
    mbar_wait(bars, B_WSF, 1);
#pragma unroll 1
    for (int s = 0; s < 4; s++) {
      float acc[24];
      brick<0>(acc, wf, sm, bars, gc);
      const bool leader = (opaque_tid() & 31) == 0;
      if (s == 3 && leader) mbar_arrive(bars + B_WSE * 8);
      epi_part(acc, 0, s);
      __syncwarp();
      if (leader) mbar_arrive(bars + (B_EVG + 8 + s) * 8);
      if (threadIdx.x == 128) TSTAMP(33 + s);
    }
  }
  {
    uint32_t wf[WREG][4];
    if (threadIdx.x == 128) TSTAMP(40);
    load_w<0>(wf, sm, bars, gc);
    mbar_wait(bars, B_WSF, 0);
#pragma unroll 1
    for (int s = 0; s < 4; s++) {
      float acc[24];
      brick<1>(acc, wf, sm, bars, xc);
      epi_part(acc, 1, s);
      __syncwarp();
      if ((opaque_tid() & 31) == 0) mbar_arrive(bars + (B_EVG + 12 + s) * 8);
      if (threadIdx.x == 128) TSTAMP(41 + s);
    }
  }
#pragma unroll 1
  for (int f = 0; f < 8; f++) finalize(sm, bars, xc, out, f >> 2, f & 3);
}
__device__ __forceinline__ void gemm_op(uint32_t sm, uint32_t bars, bf16* out) {
  GCur<1> xc; xc.init(0);
#pragma unroll 1
  for (int br = 0; br < 2; br++) {
    uint32_t wf[WREG][4];
    if (threadIdx.x == 128) TSTAMP(32 + br * 8);
    load_w<1>(wf, sm, bars, xc);
    mbar_wait(bars, B_WSF, (br + 1) & 1);
#pragma unroll 1
    for (int s = 0; s < 4; s++) {
      float acc[24];
      brick<1>(acc, wf, sm, bars, xc);
      const bool leader = (opaque_tid() & 31) == 0;
      if (s == 3 && leader) mbar_arrive(bars + B_WSE * 8);
      epi_part(acc, br, s);
      __syncwarp();
      if (leader) mbar_arrive(bars + (B_EVG + 8 + br * 4 + s) * 8);
      if (threadIdx.x == 128) TSTAMP(33 + br * 8 + s);
    }
  }
#pragma unroll 1
  for (int f = 0; f < 8; f++) finalize(sm, bars, xc, out, f >> 2, f & 3);
}

__global__ void __launch_bounds__(NTHREADS, 1) fused_kernel(const __grid_constant__ Params P) {
  extern __shared__ uint8_t smem_raw[];
  const uint32_t sm = (smem_u32(smem_raw) + 1023u) & ~1023u;
  const uint32_t bars = sm + SM_BAR;
  const int tid = threadIdx.x, wg = tid >> 7, warp = (tid >> 5) & 3, lane = tid & 31;
  const int cta = blockIdx.x;
  const int h = cta >> 2, j = cta & 3;
  const int n_t = h & 3, kc = h >> 2;

  if (tid == 0) {
    TSTAMP(0);
    asm volatile("st.shared.u32 [%0], %1;" ::"r"(bars + B_END * 8), "r"((uint32_t)clock()) : "memory");
  }
  if (tid < B_END) {
    int cnt = 1;
    if (tid >= B_KVE && tid < B_GF) cnt = 12;
    else if (tid >= B_GE && tid < B_EVA) cnt = 8;
    else if (tid >= B_EVA && tid < B_WSF) cnt = (tid == B_EVA + UA) ? 12 : 4;
    else if (tid == B_WSE || tid == B_WQE || tid == B_Q0) cnt = 8;
    else if (tid >= B_XE && tid < B_RDY) cnt = 8;
    mbar_init(bars + tid * 8, cnt);
    asm volatile("fence.mbarrier_init.release.cluster;" ::: "memory");
  }
  __syncthreads();

  if (wg == 3) {
    asm volatile("setmaxnreg.dec.sync.aligned.u32 32;");
    if (warp == 0 && lane == 0) {
      prefetch_tmap(&P.kB); prefetch_tmap(&P.vB); prefetch_tmap(&P.qB);
      prefetch_tmap(&P.kA); prefetch_tmap(&P.vA); prefetch_tmap(&P.qA);
      mbar_wait(bars, B_WQE, 0);
      const uint64_t pol = policy_evict_first();
      KCur c; c.init(0);
#pragma unroll 1
      for (int u = 0; u < 5; u++) {
        const bool isA = (u == UA);
        const int b = isA ? 4 * j + (h & 3) : 4 * j + (u < UA ? u : u - 1);
        const CUtensorMap* mk_ = isA ? &P.kA : &P.kB;
        const CUtensorMap* mv_ = isA ? &P.vA : &P.vB;
        const int row0 = isA ? (b * NGRP + kc) * SK : (b * NH + h) * SK;
        const int qslot = c.slot;
        if (u > 0) {
          mbar_wait(bars, B_KVE + c.slot, c.phase ^ 1);
          c.next();
        }
        bool qdone = (u == 0);
#pragma unroll 1
        for (int t = 0; t < 16; t++) {
          while (!qdone) {
            if (mbar_test(bars + (B_RDY + u) * 8, 0)) {
              mbar_expect_tx(bars + (B_KVF + qslot) * 8, SLOT);
              tma_3d(sm + SM_KV + qslot * SLOT, isA ? &P.qA : &P.qB, 0, isA ? (b * NGRP + kc) * 192 : (b * NH + h) * SQ, 0,
                     bars + (B_KVF + qslot) * 8);
              qdone = true;
              break;
            }
            if (mbar_test(bars + (B_KVE + c.slot) * 8, c.phase ^ 1)) break;
            if (expired(bars)) break;
            __nanosleep(64);
          }
          mbar_wait(bars, B_KVE + c.slot, c.phase ^ 1);
          mbar_expect_tx(bars + (B_KVF + c.slot) * 8, SLOT);
          tma_3d_hint(sm + SM_KV + c.slot * SLOT, (t & 1) ? mv_ : mk_, 0, row0 + (((t >> 1) + ROT(cta)) & 7) * 64, 0, bars + (B_KVF + c.slot) * 8, pol);
          c.next();
        }
      }
    } else if (warp == 1 && lane == 0) {
      prefetch_tmap(&P.wqB); prefetch_tmap(&P.wqBt); prefetch_tmap(&P.xB);
      GCur<0> c; c.init(0);
      uint32_t wsph = 1;
      auto ldWS = [&](const CUtensorMap* mt, int k0, int nch) {
        mbar_wait(bars, B_WSE, wsph);
        wsph ^= 1;
        mbar_expect_tx(bars + B_WSF * 8, (32 - WREG) * 4096);
        tma_3d(sm + SM_WS, mt, 0, k0 + WREG * 16, nch, bars + B_WSF * 8);
      };
      auto ldX = [&](const CUtensorMap* m, int row0, int ch0) {
#pragma unroll 1
        for (int i = 0; i < 4; i++) {
          mbar_wait(bars, c.empty(), c.phase ^ 1);
          mbar_expect_tx(bars + c.full() * 8, XBYTES);
          tma_3d(sm + c.off(), m, 0, row0, ch0 + 2 * i, bars + c.full() * 8);
          c.next();
        }
      };
      auto ldW = [&](const CUtensorMap* m, const CUtensorMap* mt, int k0, int nch) {
#pragma unroll 1
        for (int i = 0; i < WREG / 3; i++) {
          if (i == NGS) ldWS(mt, k0, nch);
          mbar_wait(bars, c.empty(), c.phase ^ 1);
          mbar_expect_tx(bars + c.full() * 8, XBYTES);
          tma_3d(sm + c.off(), m, 0, k0 + i * 48, nch, bars + c.full() * 8);
          c.next();
        }
      };
      {
        GCur<2> wc; wc.init(0);
#pragma unroll 1
        for (int i = 0; i < WREG / 3; i++) {
          mbar_expect_tx(bars + wc.full() * 8, XBYTES);
          tma_3d(sm + wc.off(), &P.wqB, 0, i * 48, 2 * h, bars + wc.full() * 8);
          wc.next();
        }
        ldWS(&P.wqBt, 0, 2 * h);
      }
#pragma unroll 1
      for (int s = 0; s < 2; s++) ldX(&P.xB, (4 * j + s) * SQ, 0);
      prefetch_tmap(&P.wqA); prefetch_tmap(&P.wqAt); prefetch_tmap(&P.xA);
      ldW(&P.wqA, &P.wqAt, 0, 2 * h);
#pragma unroll 1
      for (int s = 0; s < 4; s++) ldX(&P.xA, (4 * j + s) * SQ, 0);
      ldW(&P.wqB, &P.wqBt, 0, 2 * h);
#pragma unroll 1
      for (int s = 2; s < 4; s++) ldX(&P.xB, (4 * j + s) * SQ, 0);
      prefetch_tmap(&P.woA); prefetch_tmap(&P.oA); prefetch_tmap(&P.woB); prefetch_tmap(&P.oB);
      prefetch_tmap(&P.woAt); prefetch_tmap(&P.woBt);
#pragma unroll 1
      for (int i = 0; i < QPAD; i++) {
        mbar_wait(bars, c.empty(), c.phase ^ 1);
        mbar_arrive(bars + c.full() * 8);
        c.next();
      }
      {
        const int bA = 4 * j + (h & 3);
        mbar_wait(bars, B_RDY + UA, 0);
        GCur<0> c0 = c;
#pragma unroll 1
        for (int i = 0; i < 3; i++) { mbar_wait(bars, c.empty(), c.phase ^ 1); c.next(); }
        mbar_expect_tx(bars + c0.full() * 8, 32768);
        tma_3d(sm + c0.off(), &P.qA, 0, (bA * NGRP + kc) * 192 + 64, 0, bars + c0.full() * 8);
        tma_3d(sm + c0.off() + 16384, &P.qA, 0, (bA * NGRP + kc) * 192 + 128, 0, bars + c0.full() * 8);
        mbar_arrive(bars + (c0.full() + 1) * 8);
        mbar_arrive(bars + (c0.full() + 2) * 8);
      }
      ldW(&P.woA, &P.woAt, kc * 512, 2 * n_t);
#pragma unroll 1
      for (int s = 0; s < 4; s++) {
        mbar_wait(bars, B_RDY + 5 + s, 0);
#pragma unroll 1
        for (int i = 0; i < 4; i++) {
          mbar_wait(bars, c.empty(), c.phase ^ 1);
          mbar_expect_tx(bars + c.full() * 8, XBYTES);
          tma_3d(sm + c.off(), &P.oA, 0, ((4 * j + s) * NGRP + kc) * 192 + i * SQ, 0, bars + c.full() * 8);
          c.next();
        }
      }
      ldW(&P.woB, &P.woBt, kc * 512, 2 * n_t);
      {
#pragma unroll 1
        for (int i = 0; i < NGS; i++) { mbar_wait(bars, c.empty(), c.phase ^ 1); c.next(); }
        GCur<1> x; x.init(0);
        bool ext_ok = false;
        auto acquire = [&]() {
          if (x.slot >= NGS && !ext_ok) { mbar_wait(bars, B_EVA + 4, 0); ext_ok = true; }
          mbar_wait(bars, x.empty(), x.phase ^ 1);
        };
#pragma unroll 1
        for (int s = 0; s < 4; s++) {
          mbar_wait(bars, B_RDY + 9 + s, 0);
#pragma unroll 1
          for (int i = 0; i < 4; i++) {
            acquire();
            mbar_expect_tx(bars + x.full() * 8, XBYTES);
            tma_3d(sm + x.off(), &P.oB, 0, ((4 * j + s) * NH + 4 * kc + i) * SQ, 0, bars + x.full() * 8);
            x.next();
          }
        }
#pragma unroll 1
        for (int f = 0; f < 8; f++) {
          mbar_wait(bars, B_RDY + 13 + f, 0);
          const uint4* src = g_part + ((size_t)((((f >> 2) * NB + 4 * j + (f & 3)) * 4 + n_t) * 8 + kc)) * (8 * 96);
          acquire();
          mbar_expect_tx(bars + x.full() * 8, XBYTES);
          bulk_g2s(sm + x.off(), src, XBYTES, bars + x.full() * 8);
          x.next();
        }
      }
    } else if (warp == 2) {
      if (lane < 2) {
        const int nev = lane == 0 ? 16 : 5;
        int e = lane == 0 ? 1 : 0;
        while (e < nev) {
          if (mbar_test(bars + ((lane == 0 ? B_EVG : B_EVA) + e) * 8, 0)) {
            __threadfence();
            if (lane == 0 && (e == 1 || e == 6 || e == 7)) {
              const int s = e == 1 ? 1 : e - 4;
              fence_proxy_async_global();
              mbar_arrive(bars + (B_RDY + (s < UA ? s : s + 1)) * 8);
            } else {
              unsigned* f;
              if (lane == 0) {
                if (e < 8) f = &g_flags.qa_cnt[((4 * j + e - 2) * NGRP + kc) * 8];
                else f = &g_flags.part_cnt[(((e < 12 ? 0 : 1) * NB + 4 * j + (e & 3)) * 4 + n_t) * 8];
              } else {
                f = (e == UA) ? &g_flags.oa_cnt[((4 * j + (h & 3)) * NGRP + kc) * 8]
                              : &g_flags.ob_cnt[((4 * j + (e < UA ? e : e - 1)) * NGRP + kc) * 8];
              }
              red_add(f, 1);
            }
            e++;
          } else {
            if (expired(bars)) break;
            __nanosleep(POLL_NS);
          }
        }
      }
    } else if (warp == 3) {
      unsigned ep1 = 0;
      if (lane == 0) {
        const unsigned e = *reinterpret_cast<volatile unsigned*>(&g_flags.epoch);
        ep1 = e + 1;
        __threadfence();
        const unsigned old = atomicAdd(&g_flags.started, 1u);
        if (old == gridDim.x - 1) {
          g_flags.started = 0;
          __threadfence();
          *reinterpret_cast<volatile unsigned*>(&g_flags.epoch) = e + 1;
        }
      }
      ep1 = __shfl_sync(0xffffffffu, ep1, 0);
      const bool mine = (lane == UA) || (lane >= 5 && lane < 21);
      const unsigned* f = &g_flags.qa_cnt[((4 * j + (h & 3)) * NGRP + kc) * 8];
      unsigned target = 4 * ep1;
      if (lane >= 5 && lane < 9) { f = &g_flags.oa_cnt[((4 * j + lane - 5) * NGRP + kc) * 8]; target = ep1; }
      else if (lane >= 9 && lane < 13) { f = &g_flags.ob_cnt[((4 * j + lane - 9) * NGRP + kc) * 8]; target = 4 * ep1; }
      else if (lane >= 13 && lane < 21) { f = &g_flags.part_cnt[((((lane - 13) >> 2) * NB + 4 * j + ((lane - 13) & 3)) * 4 + n_t) * 8]; target = 8 * ep1; }
      bool done = !mine;
      while (true) {
        if (!done && (int)(ld_acquire(f) - target) >= 0) {
          fence_proxy_async_global();
          mbar_arrive(bars + (B_RDY + lane) * 8);
          done = true;
        }
        if (__all_sync(0xffffffffu, done)) break;
        if (__any_sync(0xffffffffu, expired(bars))) break;
        __nanosleep(POLL_NS);
      }
    }
  } else {
    asm volatile("setmaxnreg.inc.sync.aligned.u32 160;");
    GCur<0> gc; gc.init(0);
    uint32_t qs = sm + SM_QS;
    int qe0 = 0;
    if (wg != 0) {
      gemm_q0(sm, bars, gc);
      gemm_q1(sm, bars, gc);
      mbar_wait(bars, B_EVA + UA - 1, 0);
#pragma unroll 1
      for (int i = 0; i < QPAD; i++) {
        mbar_wait(bars, gc.full(), gc.phase);
        if (lane == 0) mbar_arrive(bars + gc.empty() * 8);
        gc.next();
      }
      qs = sm + gc.off() + (wg - 1) * 16384;
      qe0 = gc.empty();
#pragma unroll 1
      for (int i = 0; i < 3; i++) { mbar_wait(bars, gc.full(), gc.phase); gc.next(); }
    }
    {
      KCur cur; cur.init(wg == 0 ? 0 : KV_POS_A);
      const int u1 = wg == 0 ? 5 : UA + 1;
#pragma unroll 1
      for (int u = (wg == 0 ? 0 : UA); u < u1; u++) {
        if (tid == 0) TSTAMP(1 + 2 * u);
        attn_unit(sm, bars, cur, u, qs);
        if (tid == 0) TSTAMP(2 + 2 * u);
      }
    }
    if (wg != 0) {
      named_bar(5, 256);
      if (lane == 0) for (int i = 0; i < 3; i++) mbar_arrive(bars + (qe0 + i) * 8);
      gemm_op_narrow(sm, bars, gc, P.out);
      if (tid == 128) TSTAMP(48);
    }
  }
}

typedef CUresult (*EncodeFn)(CUtensorMap*, CUtensorMapDataType, cuuint32_t, void*, const cuuint64_t*, const cuuint64_t*,
                             const cuuint32_t*, const cuuint32_t*, CUtensorMapInterleave, CUtensorMapSwizzle,
                             CUtensorMapL2promotion, CUtensorMapFloatOOBfill);

static bool make_map(EncodeFn fn, CUtensorMap* m, const void* base, uint64_t rows, uint64_t row_elems, uint32_t box_rows) {
  cuuint64_t dims[3] = {64, rows, row_elems / 64};
  cuuint64_t strides[2] = {row_elems * 2, 128};
  cuuint32_t box[3] = {64, box_rows, 2};
  cuuint32_t estr[3] = {1, 1, 1};
  CUresult r = fn(m, CU_TENSOR_MAP_DATA_TYPE_BFLOAT16, 3, const_cast<void*>(base), dims, strides, box, estr,
                  CU_TENSOR_MAP_INTERLEAVE_NONE, CU_TENSOR_MAP_SWIZZLE_128B, CU_TENSOR_MAP_L2_PROMOTION_L2_256B,
                  CU_TENSOR_MAP_FLOAT_OOB_FILL_NONE);
  if (r != CUDA_SUCCESS) fprintf(stderr, "cuTensorMapEncodeTiled failed: %d\n", (int)r);
  return r == CUDA_SUCCESS;
}

}

extern "C" void kernel_launch(void* const* d_in, const int* in_sizes, int n_in, void* d_out, int out_size) {
  using namespace mk;
  static Params P;
  static bool init = false;
  static void* cached[11] = {0};
  bool same = init;
  for (int i = 0; i < 10; i++) same = same && (cached[i] == d_in[i]);
  same = same && (cached[10] == d_out);
  if (!same) {
    void* fnp = nullptr;
    cudaDriverEntryPointQueryResult qr;
    cudaGetDriverEntryPoint("cuTensorMapEncodeTiled", &fnp, cudaEnableDefault, &qr);
    EncodeFn fn = (EncodeFn)fnp;
    void *qa, *qb;
    cudaGetSymbolAddress(&qa, g_QA); cudaGetSymbolAddress(&qb, g_QB);
    make_map(fn, &P.xA, d_in[0], 768, 512, 48);
    make_map(fn, &P.kA, d_in[1], (uint64_t)NB * NGRP * SK, 128, 64);
    make_map(fn, &P.vA, d_in[2], (uint64_t)NB * NGRP * SK, 128, 64);
    make_map(fn, &P.wqA, d_in[3], 512, 4096, 48);
    make_map(fn, &P.wqAt, d_in[3], 512, 4096, (32 - WREG) * 16);
    make_map(fn, &P.woA, d_in[4], 4096, 512, 48);
    make_map(fn, &P.woAt, d_in[4], 4096, 512, (32 - WREG) * 16);
    make_map(fn, &P.xB, d_in[5], 768, 512, 48);
    make_map(fn, &P.kB, d_in[6], (uint64_t)NB * NH * SK, 128, 64);
    make_map(fn, &P.vB, d_in[7], (uint64_t)NB * NH * SK, 128, 64);
    make_map(fn, &P.wqB, d_in[8], 512, 4096, 48);
    make_map(fn, &P.wqBt, d_in[8], 512, 4096, (32 - WREG) * 16);
    make_map(fn, &P.woB, d_in[9], 4096, 512, 48);
    make_map(fn, &P.woBt, d_in[9], 4096, 512, (32 - WREG) * 16);
    make_map(fn, &P.qA, qa, (uint64_t)NB * NGRP * 192, 128, 64);
    make_map(fn, &P.qB, qb, (uint64_t)NB * NH * SQ + 16, 128, 64);
    make_map(fn, &P.oA, qa, (uint64_t)NB * NGRP * 192, 128, 48);
    make_map(fn, &P.oB, qb, (uint64_t)NB * NH * SQ + 16, 128, 48);
    P.out = (bf16*)d_out;
    cudaFuncSetAttribute(fused_kernel, cudaFuncAttributeMaxDynamicSharedMemorySize, SM_TOTAL);
    for (int i = 0; i < 10; i++) cached[i] = d_in[i];
    cached[10] = d_out;
    init = true;
  }
  fused_kernel<<<NCTA, NTHREADS, SM_TOTAL>>>(P);
}
```

```cpp
#include <cuda_runtime.h>
#include <cuda_bf16.h>
#include <cuda.h>
#include <stdint.h>
#include <stdio.h>
#include <stdlib.h>

namespace mk {

typedef __nv_bfloat16 bf16;

constexpr int NB = 16, SQ = 48, NH = 32, NGRP = 8, SK = 512, DH = 128;
constexpr int SLOT = 16384;
#define NKVS 4
#define NGS 10
#define POLL_NS 64
#define WAIT_HINT_NS 100000u
constexpr int XBYTES = 12288;
constexpr int WREG = 27;
constexpr int SM_QS = 0;
constexpr int SM_KV = 16384;
constexpr int SM_G = SM_KV + NKVS * SLOT;
constexpr int SM_WS = SM_G + NGS * XBYTES;
constexpr int SM_BAR = SM_WS + (32 - WREG) * 4096;
constexpr int SM_TOTAL = SM_BAR + 1024 + 1024;
constexpr int NEXT = (NKVS * SLOT) / XBYTES;
constexpr int NWIDE = NGS + NEXT;
constexpr int SM_EXT = SM_G - NEXT * XBYTES;
constexpr int PAD0 = NEXT >= WREG / 3 ? 0 : WREG / 3 - NEXT;
constexpr int QP_ENTRIES = PAD0 + 8 * 4 + 2 * (WREG / 3);
#define UA_POS 2
constexpr int UA = UA_POS;
constexpr int KV_POS_A = 16 + 17 * (UA - 1);
constexpr int QPAD = (QP_ENTRIES % NGS + 3 > NGS) ? NGS - QP_ENTRIES % NGS : 0;
constexpr int NCTA = 128;
constexpr int NTHREADS = 512;

constexpr int B_KVF = 0;
constexpr int B_KVE = B_KVF + NKVS;
constexpr int B_GF = B_KVE + NKVS;
constexpr int B_GE = B_GF + NGS;
constexpr int B_EVG = B_GE + NGS;
constexpr int B_EVA = B_EVG + 16;
constexpr int B_WSF = B_EVA + 5;
constexpr int B_WSE = B_WSF + 1;
constexpr int B_WQF = B_WSE + 1;
constexpr int B_WQE = B_WQF + WREG / 3;
constexpr int B_XF = B_WQE + 1;
constexpr int B_XE = B_XF + NWIDE;
constexpr int B_RDY = B_XE + NWIDE;
constexpr int B_Q0 = B_RDY + 21;
constexpr int B_END = B_Q0 + 1;
static_assert(B_END * 8 + 16 <= 1024 && B_END <= 512, "barrier region");
static_assert(SM_TOTAL <= 232448, "smem");

struct alignas(64) Params {
  CUtensorMap kA, vA, kB, vB, qA, qB;
  CUtensorMap xA, xB;
  CUtensorMap oA, oB;
  CUtensorMap wqA, wqB, woA, woB;
  CUtensorMap wqAt, wqBt, woAt, woBt;
  bf16* out;
};

__device__ bf16 g_QA[NB * NGRP * 192 * DH];
__device__ bf16 g_QB[NB * NH * SQ * DH + 16 * DH];
__device__ uint4 g_part[2 * NB * 4 * 8 * 8 * 96];
struct Flags {
  unsigned epoch;
  unsigned pad0[31];
  unsigned started;
  unsigned pad1[31];
  unsigned qa_cnt[NB * NGRP * 8];
  unsigned oa_cnt[NB * NGRP * 8];
  unsigned ob_cnt[NB * NGRP * 8];
  unsigned part_cnt[2 * NB * 4 * 8];
};
__device__ Flags g_flags;
__constant__ uint32_t c_zero;

#define TSTAMP(idx) do {} while (0)

__device__ __forceinline__ uint32_t smem_u32(const void* p) { return (uint32_t)__cvta_generic_to_shared(p); }
__device__ __forceinline__ void mbar_init(uint32_t bar, uint32_t cnt) {
  asm volatile("mbarrier.init.shared::cta.b64 [%0], %1;" ::"r"(bar), "r"(cnt) : "memory");
}
__device__ __forceinline__ void mbar_expect_tx(uint32_t bar, uint32_t bytes) {
  asm volatile("mbarrier.arrive.expect_tx.shared::cta.b64 _, [%0], %1;" ::"r"(bar), "r"(bytes) : "memory");
}
__device__ __forceinline__ void mbar_arrive(uint32_t bar) {
  asm volatile("mbarrier.arrive.shared::cta.b64 _, [%0];" ::"r"(bar) : "memory");
}
__device__ __forceinline__ void mbar_arrive_n(uint32_t bar, uint32_t n) {
  asm volatile("mbarrier.arrive.shared::cta.b64 _, [%0], %1;" ::"r"(bar), "r"(n) : "memory");
}
__device__ __forceinline__ bool mbar_try(uint32_t bar, uint32_t parity) {
  uint32_t ok;
  asm volatile("{\n.reg .pred p;\nmbarrier.try_wait.parity.shared::cta.b64 p, [%1], %2, %3;\nselp.u32 %0, 1, 0, p;\n}"
               : "=r"(ok) : "r"(bar), "r"(parity), "r"(WAIT_HINT_NS) : "memory");
  return ok != 0;
}
__device__ __forceinline__ bool mbar_test(uint32_t bar, uint32_t parity) {
  uint32_t ok;
  asm volatile("{\n.reg .pred p;\nmbarrier.test_wait.parity.shared::cta.b64 p, [%1], %2;\nselp.u32 %0, 1, 0, p;\n}"
               : "=r"(ok) : "r"(bar), "r"(parity) : "memory");
  return ok != 0;
}
__device__ __forceinline__ bool expired(uint32_t bars) {
  uint32_t t0, t1;
  asm volatile("ld.volatile.shared.u32 %0, [%1];" : "=r"(t0) : "r"(bars + B_END * 8));
  asm volatile("mov.u32 %0, %%clock;" : "=r"(t1));
  return (t1 - t0) > 1900000000u;
}
__device__ __forceinline__ int opaque_tid() {
  int t;
  asm volatile("mov.u32 %0, %%tid.x;" : "=r"(t));
  return t;
}
__device__ __forceinline__ int opaque_cta() {
  int t;
  asm volatile("mov.u32 %0, %%ctaid.x;" : "=r"(t));
  return t;
}
__device__ __forceinline__ void mbar_wait(uint32_t bars, int idx, uint32_t parity) {
  while (!mbar_try(bars + idx * 8, parity)) {
    if (expired(bars)) break;
  }
}
__device__ __forceinline__ unsigned ld_acquire(const unsigned* p) {
  unsigned v;
  asm volatile("ld.acquire.gpu.global.u32 %0, [%1];" : "=r"(v) : "l"(p) : "memory");
  return v;
}
__device__ __forceinline__ void red_add(unsigned* p, unsigned v) {
  asm volatile("red.relaxed.gpu.global.add.u32 [%0], %1;" ::"l"(p), "r"(v) : "memory");
}
__device__ __forceinline__ void fence_proxy_async() { asm volatile("fence.proxy.async.shared::cta;" ::: "memory"); }
__device__ __forceinline__ void fence_proxy_async_global() { asm volatile("fence.proxy.async.global;" ::: "memory"); }
__device__ __forceinline__ void tma_3d(uint32_t dst, const CUtensorMap* map, int c0, int c1, int c2, uint32_t bar) {
  asm volatile(
      "cp.async.bulk.tensor.3d.shared::cluster.global.mbarrier::complete_tx::bytes [%0], [%1, {%3, %4, %5}], [%2];" ::"r"(dst),
      "l"(map), "r"(bar), "r"(c0), "r"(c1), "r"(c2)
      : "memory");
}
__device__ __forceinline__ void tma_3d_hint(uint32_t dst, const CUtensorMap* map, int c0, int c1, int c2, uint32_t bar, uint64_t pol) {
  asm volatile(
      "cp.async.bulk.tensor.3d.shared::cluster.global.mbarrier::complete_tx::bytes.L2::cache_hint [%0], [%1, {%3, %4, %5}], [%2], %6;" ::"r"(dst),
      "l"(map), "r"(bar), "r"(c0), "r"(c1), "r"(c2), "l"(pol)
      : "memory");
}
__device__ __forceinline__ uint64_t policy_evict_first() {
  uint64_t pol;
  asm volatile("createpolicy.fractional.L2::evict_first.b64 %0, 1.0;" : "=l"(pol));
  return pol;
}
__device__ __forceinline__ void bulk_g2s(uint32_t dst, const void* src, uint32_t bytes, uint32_t bar) {
  asm volatile("cp.async.bulk.shared::cluster.global.mbarrier::complete_tx::bytes [%0], [%1], %2, [%3];" ::"r"(dst), "l"(src),
               "r"(bytes), "r"(bar)
               : "memory");
}
__device__ __forceinline__ void prefetch_tmap(const CUtensorMap* map) {
  asm volatile("prefetch.tensormap [%0];" ::"l"(map) : "memory");
}
__device__ __forceinline__ void ldsm_x4_t(uint32_t (&r)[4], uint32_t addr) {
  asm volatile("ldmatrix.sync.aligned.m8n8.x4.trans.shared.b16 {%0,%1,%2,%3}, [%4];"
               : "=r"(r[0]), "=r"(r[1]), "=r"(r[2]), "=r"(r[3]) : "r"(addr) : "memory");
}
__device__ __forceinline__ void stsm_x4(uint32_t addr, uint32_t r0, uint32_t r1, uint32_t r2, uint32_t r3) {
  asm volatile("stmatrix.sync.aligned.m8n8.x4.shared.b16 [%0], {%1,%2,%3,%4};" ::"r"(addr), "r"(r0), "r"(r1), "r"(r2), "r"(r3)
               : "memory");
}
__device__ __forceinline__ uint4 lds128(uint32_t addr) {
  uint4 v;
  asm volatile("ld.shared.v4.u32 {%0,%1,%2,%3}, [%4];" : "=r"(v.x), "=r"(v.y), "=r"(v.z), "=r"(v.w) : "r"(addr) : "memory");
  return v;
}
__device__ __forceinline__ void sts128(uint32_t addr, uint4 v) {
  asm volatile("st.shared.v4.u32 [%0], {%1,%2,%3,%4};" ::"r"(addr), "r"(v.x), "r"(v.y), "r"(v.z), "r"(v.w) : "memory");
}
__device__ __forceinline__ uint32_t dep_on(uint32_t addr, uint32_t loaded) { return addr + (loaded & c_zero); }
__device__ __forceinline__ void named_bar(int id, int n) { asm volatile("bar.sync %0, %1;" ::"r"(id), "r"(n) : "memory"); }
__device__ __forceinline__ void wg_fence() { asm volatile("wgmma.fence.sync.aligned;" ::: "memory"); }
__device__ __forceinline__ void wg_commit() { asm volatile("wgmma.commit_group.sync.aligned;" ::: "memory"); }
template <int N>
__device__ __forceinline__ void wg_wait() { asm volatile("wgmma.wait_group.sync.aligned %0;" ::"n"(N) : "memory"); }
template <int N>
__device__ __forceinline__ void fence_regs(float (&a)[N]) {
#pragma unroll
  for (int i = 0; i < N; i++) asm volatile("" : "+f"(a[i])::"memory");
}
__device__ __forceinline__ uint64_t make_desc(uint32_t addr, uint32_t lbo, uint32_t sbo) {
  return (uint64_t)((addr & 0x3FFFF) >> 4) | ((uint64_t)(lbo >> 4) << 16) | ((uint64_t)(sbo >> 4) << 32) | (1ull << 62);
}
__device__ __forceinline__ uint32_t pack_bf16(float lo, float hi) {
  uint32_t r;
  asm("cvt.rn.bf16x2.f32 %0, %1, %2;" : "=r"(r) : "f"(hi), "f"(lo));
  return r;
}
__device__ __forceinline__ float ex2(float x) {
  float y;
  asm("ex2.approx.ftz.f32 %0, %1;" : "=f"(y) : "f"(x));
  return y;
}
__device__ __forceinline__ float rcp(float x) {
  float y;
  asm("rcp.approx.ftz.f32 %0, %1;" : "=f"(y) : "f"(x));
  return y;
}
__device__ __forceinline__ uint32_t movmatrix_t(uint32_t x) {
  uint32_t y;
  asm volatile("movmatrix.sync.aligned.m8n8.trans.b16 %0, %1;" : "=r"(y) : "r"(x));
  return y;
}

#define ACC8(d, o) "+f"(d[o]), "+f"(d[o + 1]), "+f"(d[o + 2]), "+f"(d[o + 3]), "+f"(d[o + 4]), "+f"(d[o + 5]), "+f"(d[o + 6]), "+f"(d[o + 7])
__device__ __forceinline__ void wgmma_n64_ss(float (&d)[32], uint64_t da, uint64_t db, int scale_d) {
  asm volatile(
      "{\n.reg .pred p;\nsetp.ne.b32 p, %34, 0;\n"
      "wgmma.mma_async.sync.aligned.m64n64k16.f32.bf16.bf16 "
      "{%0,%1,%2,%3,%4,%5,%6,%7,%8,%9,%10,%11,%12,%13,%14,%15,%16,%17,%18,%19,%20,%21,%22,%23,%24,%25,%26,%27,%28,%29,%30,%31},"
      "%32, %33, p, 1, 1, 0, 0;\n}"
      : ACC8(d, 0), ACC8(d, 8), ACC8(d, 16), ACC8(d, 24)
      : "l"(da), "l"(db), "r"(scale_d));
}
__device__ __forceinline__ void wgmma_n128_t(float (&d)[64], const uint32_t (&a)[4], uint64_t desc, int scale_d) {
  asm volatile(
      "{\n.reg .pred p;\nsetp.ne.b32 p, %69, 0;\n"
      "wgmma.mma_async.sync.aligned.m64n128k16.f32.bf16.bf16 "
      "{%0,%1,%2,%3,%4,%5,%6,%7,%8,%9,%10,%11,%12,%13,%14,%15,%16,%17,%18,%19,%20,%21,%22,%23,%24,%25,%26,%27,%28,%29,%30,%31,"
      "%32,%33,%34,%35,%36,%37,%38,%39,%40,%41,%42,%43,%44,%45,%46,%47,%48,%49,%50,%51,%52,%53,%54,%55,%56,%57,%58,%59,%60,%61,%62,%63},"
      "{%64,%65,%66,%67}, %68, p, 1, 1, 1;\n}"
      : ACC8(d, 0), ACC8(d, 8), ACC8(d, 16), ACC8(d, 24), ACC8(d, 32), ACC8(d, 40), ACC8(d, 48), ACC8(d, 56)
      : "r"(a[0]), "r"(a[1]), "r"(a[2]), "r"(a[3]), "l"(desc), "r"(scale_d));
}
__device__ __forceinline__ void wgmma_n48(float (&d)[24], const uint32_t (&a)[4], uint64_t desc, int scale_d) {
  asm volatile(
      "{\n.reg .pred p;\nsetp.ne.b32 p, %29, 0;\n"
      "wgmma.mma_async.sync.aligned.m64n48k16.f32.bf16.bf16 "
      "{%0,%1,%2,%3,%4,%5,%6,%7,%8,%9,%10,%11,%12,%13,%14,%15,%16,%17,%18,%19,%20,%21,%22,%23},"
      "{%24,%25,%26,%27}, %28, p, 1, 1, 0;\n}"
      : ACC8(d, 0), ACC8(d, 8), ACC8(d, 16)
      : "r"(a[0]), "r"(a[1]), "r"(a[2]), "r"(a[3]), "l"(desc), "r"(scale_d));
}
__device__ __forceinline__ void wgmma_n48_ss(float (&d)[24], uint64_t descA, uint64_t descB) {
  asm volatile(
      "{\n.reg .pred p;\nsetp.ne.b32 p, 1, 0;\n"
      "wgmma.mma_async.sync.aligned.m64n48k16.f32.bf16.bf16 "
      "{%0,%1,%2,%3,%4,%5,%6,%7,%8,%9,%10,%11,%12,%13,%14,%15,%16,%17,%18,%19,%20,%21,%22,%23},"
      "%24, %25, p, 1, 1, 1, 0;\n}"
      : ACC8(d, 0), ACC8(d, 8), ACC8(d, 16)
      : "l"(descA), "l"(descB));
}

struct KCur {
  int slot;
  uint32_t phase;
  __device__ __forceinline__ void init(int count) { slot = count % NKVS; phase = (count / NKVS) & 1; }
  __device__ __forceinline__ void next() { if (++slot == NKVS) { slot = 0; phase ^= 1; } }
};
template <int MODE>
struct GCur {
  int slot;
  uint32_t phase;
  static constexpr int N = MODE == 0 ? NGS : (MODE == 1 ? NWIDE : WREG / 3);
  __device__ __forceinline__ void init(int count) { slot = count % N; phase = (count / N) & 1; }
  __device__ __forceinline__ void next() { if (++slot == N) { slot = 0; phase ^= 1; } }
  __device__ __forceinline__ uint32_t off() const {
    if (MODE == 0) return SM_G + slot * XBYTES;
    if (MODE == 1) return SM_EXT + (slot < NGS ? slot + NEXT : slot - NGS) * XBYTES;
    return SM_EXT + slot * XBYTES;
  }
  __device__ __forceinline__ int full() const { return (MODE == 0 ? B_GF : (MODE == 1 ? B_XF : B_WQF)) + slot; }
  __device__ __forceinline__ int empty() const { return MODE == 2 ? B_WQE : (MODE == 0 ? B_GE : B_XE) + slot; }
};

constexpr float SM_C = 0.08838834764831845f * 1.4426950408889634f;
constexpr float RESCALE_T = 8.0f;

__device__ __forceinline__ void softmax_step(const float (&s)[32], uint32_t (&pf)[4][4], float (&o)[64], float& m0, float& m1,
                                             float& l0, float& l1, bool first) {
  float mx0 = fmaxf(s[0], s[1]), mx1 = fmaxf(s[2], s[3]);
#pragma unroll
  for (int j = 1; j < 8; j++) {
    mx0 = fmaxf(mx0, fmaxf(s[4 * j], s[4 * j + 1]));
    mx1 = fmaxf(mx1, fmaxf(s[4 * j + 2], s[4 * j + 3]));
  }
  mx0 = fmaxf(mx0, __shfl_xor_sync(0xffffffffu, mx0, 1));
  mx1 = fmaxf(mx1, __shfl_xor_sync(0xffffffffu, mx1, 1));
  mx0 = fmaxf(mx0, __shfl_xor_sync(0xffffffffu, mx0, 2));
  mx1 = fmaxf(mx1, __shfl_xor_sync(0xffffffffu, mx1, 2));
  const bool grow = !((mx0 - m0) * SM_C <= RESCALE_T) || !((mx1 - m1) * SM_C <= RESCALE_T);
  if (__any_sync(0xffffffffu, grow)) {
    const float mn0 = fmaxf(m0, mx0), mn1 = fmaxf(m1, mx1);
    const float a0 = ex2((m0 - mn0) * SM_C), a1 = ex2((m1 - mn1) * SM_C);
    m0 = mn0; m1 = mn1;
    l0 *= a0; l1 *= a1;
    if (!first) {
#pragma unroll
      for (int j = 0; j < 16; j++) {
        o[4 * j] *= a0; o[4 * j + 1] *= a0; o[4 * j + 2] *= a1; o[4 * j + 3] *= a1;
      }
    }
  }
  const float mc0 = m0 * SM_C, mc1 = m1 * SM_C;
#pragma unroll
  for (int j = 0; j < 8; j++) {
    const float p0 = ex2(fmaf(s[4 * j], SM_C, -mc0)), p1 = ex2(fmaf(s[4 * j + 1], SM_C, -mc0));
    const float p2 = ex2(fmaf(s[4 * j + 2], SM_C, -mc1)), p3 = ex2(fmaf(s[4 * j + 3], SM_C, -mc1));
    l0 += p0 + p1; l1 += p2 + p3;
    pf[j >> 1][(j & 1) * 2 + 0] = pack_bf16(p0, p1);
    pf[j >> 1][(j & 1) * 2 + 1] = pack_bf16(p2, p3);
  }
}

__device__ __forceinline__ void attn_unit(uint32_t sm, uint32_t bars, KCur& cur, int u, uint32_t qs) {
  const int tid_ = opaque_tid();
  const bool leader = (tid_ & 31) == 0;
  const bool isA = (u == UA);
  const uint32_t narr = isA ? 1 : 3;
  const bool active = isA || (tid_ >> 5) < 3;
  if (u == 0) {
    mbar_wait(bars, B_Q0, 0);
  } else {
    mbar_wait(bars, B_KVF + cur.slot, cur.phase);
    uint32_t rel = bars + (B_KVE + cur.slot) * 8;
    if (tid_ < 128) {
      named_bar(1, 128);
      const uint32_t src = sm + SM_KV + cur.slot * SLOT + tid_ * 16, dst = qs + tid_ * 16;
      uint32_t x = 0;
#pragma unroll
      for (int i = 0; i < 8; i++) {
        const uint4 v = lds128(src + i * 2048);
        sts128(dst + i * 2048, v);
        x ^= v.x;
      }
      rel = dep_on(rel, x);
      fence_proxy_async();
      named_bar(1, 128);
    }
    if (leader) mbar_arrive_n(rel, narr);
    cur.next();
  }
  float o[64];
  float s[32];
  float m0 = -INFINITY, m1 = -INFINITY, l0 = 0.f, l1 = 0.f;
  mbar_wait(bars, B_KVF + cur.slot, cur.phase);
  wg_fence();
#pragma unroll
  for (int ks = 0; ks < 8; ks++)
    wgmma_n64_ss(s, make_desc(qs + (ks >> 2) * 8192 + (ks & 3) * 32, 16, 1024),
                 make_desc(sm + SM_KV + cur.slot * SLOT + (ks >> 2) * 8192 + (ks & 3) * 32, 16, 1024), ks > 0);
  wg_commit();
  wg_wait<0>();
  fence_regs(s);
  if (leader) mbar_arrive_n(bars + (B_KVE + cur.slot) * 8, narr);
  cur.next();
#pragma unroll 1
  for (int t = 0; t < 8; t++) {
    uint32_t pf[4][4];
    if (active) softmax_step(s, pf, o, m0, m1, l0, l1, t == 0);
    else {
#pragma unroll
      for (int k = 0; k < 4; k++) { pf[k][0] = 0; pf[k][1] = 0; pf[k][2] = 0; pf[k][3] = 0; }
    }
    const int vs = cur.slot; const uint32_t vp = cur.phase; cur.next();
    mbar_wait(bars, B_KVF + vs, vp);
    wg_fence();
#pragma unroll
    for (int kk = 0; kk < 4; kk++)
      wgmma_n128_t(o, pf[kk], make_desc(sm + SM_KV + vs * SLOT + kk * 2048, 8192, 1024), (t > 0) || (kk > 0));
    wg_commit();
    if (t < 7) {
      const int ks_ = cur.slot;
      mbar_wait(bars, B_KVF + ks_, cur.phase);
      cur.next();
      wg_fence();
#pragma unroll
      for (int ks = 0; ks < 8; ks++)
        wgmma_n64_ss(s, make_desc(qs + (ks >> 2) * 8192 + (ks & 3) * 32, 16, 1024),
                     make_desc(sm + SM_KV + ks_ * SLOT + (ks >> 2) * 8192 + (ks & 3) * 32, 16, 1024), ks > 0);
      wg_commit();
      wg_wait<1>();
      if (leader) mbar_arrive_n(bars + (B_KVE + vs) * 8, narr);
      wg_wait<0>();
      if (leader) mbar_arrive_n(bars + (B_KVE + ks_) * 8, narr);
    } else {
      wg_wait<0>();
      if (leader) mbar_arrive_n(bars + (B_KVE + vs) * 8, narr);
    }
    fence_regs(s); fence_regs(o);
  }
  if (active) {
    l0 += __shfl_xor_sync(0xffffffffu, l0, 1); l1 += __shfl_xor_sync(0xffffffffu, l1, 1);
    l0 += __shfl_xor_sync(0xffffffffu, l0, 2); l1 += __shfl_xor_sync(0xffffffffu, l1, 2);
    const float i0 = rcp(l0), i1 = rcp(l1);
    const int tid = opaque_tid(), cta = opaque_cta();
    const int lane = tid & 31, w4 = (tid >> 5) & 3;
    named_bar(2 + (tid >> 7), isA ? 128 : 96);
    const uint32_t stg = qs + w4 * 4096;
    {
      const int mi = lane >> 3, row = (mi & 1) * 8 + (lane & 7);
#pragma unroll
      for (int jp = 0; jp < 8; jp++) {
        const int chunk = 2 * jp + (mi >> 1);
        stsm_x4(stg + row * 256 + ((chunk ^ (row & 7)) << 4), pack_bf16(o[8 * jp] * i0, o[8 * jp + 1] * i0),
                pack_bf16(o[8 * jp + 2] * i1, o[8 * jp + 3] * i1), pack_bf16(o[8 * jp + 4] * i0, o[8 * jp + 5] * i0),
                pack_bf16(o[8 * jp + 6] * i1, o[8 * jp + 7] * i1));
      }
    }
    __syncwarp();
    const int h = cta >> 2, jg = cta & 3;
    const int r0 = (tid >> 5) * 16;
    bf16* orow = isA ? g_QA + (size_t)(((4 * jg + (h & 3)) * NGRP + (h >> 2)) * 192 + r0) * DH
                     : g_QB + (size_t)(((4 * jg + (u < UA ? u : u - 1)) * NH + h) * SQ + r0) * DH;
#pragma unroll 2
    for (int i = 0; i < 8; i++) {
      const int row = 2 * i + (lane >> 4), chunk = lane & 15;
      const uint4 v = lds128(stg + row * 256 + ((chunk ^ (row & 7)) << 4));
      *reinterpret_cast<uint4*>(orow + row * DH + chunk * 8) = v;
    }
  }
  __syncwarp();
  if ((opaque_tid() & 31) == 0) mbar_arrive(bars + (B_EVA + u) * 8);
}

template <int MODE>
__device__ __forceinline__ void load_w(uint32_t (&wf)[WREG][4], uint32_t sm, uint32_t bars, GCur<MODE>& cur) {
  const int tid = opaque_tid();
  const int lane = tid & 31, warp = (tid >> 5) & 3, half = (tid >> 7) - 1;
  const int mi = lane >> 3, rr = lane & 7;
  const int chunk = warp * 2 + (mi & 1);
  const uint32_t off = sm + half * 6144 + ((mi >> 1) * 8 + rr) * 128 + ((chunk ^ rr) << 4);
  uint32_t all = 0;
#pragma unroll
  for (int c = 0; c < WREG / 3; c++) {
    mbar_wait(bars, cur.full(), cur.phase);
    const uint32_t base = off + cur.off();
#pragma unroll
    for (int ks = 0; ks < 3; ks++) ldsm_x4_t(wf[c * 3 + ks], base + ks * 2048);
    const uint32_t x = wf[c * 3][0] ^ wf[c * 3 + 1][0] ^ wf[c * 3 + 2][0];
    if (MODE == 2) {
      all ^= x;
    } else {
      const uint32_t rel = dep_on(bars + cur.empty() * 8, x);
      __syncwarp();
      if (lane == 0) mbar_arrive(rel);
    }
    cur.next();
  }
  if (MODE == 2) {
    const uint32_t rel = dep_on(bars + B_WQE * 8, all);
    __syncwarp();
    if (lane == 0) mbar_arrive(rel);
  }
}

template <int MODE>
__device__ __forceinline__ void brick(float (&acc)[24], const uint32_t (&wf)[WREG][4], uint32_t sm, uint32_t bars, GCur<MODE>& cur) {
  int prev_empty = 0;
  const int tid = opaque_tid();
  const bool leader = (tid & 31) == 0;
  const uint32_t ws = sm + SM_WS + ((tid >> 7) - 1) * ((32 - WREG) * 2048);
#pragma unroll
  for (int i = 0; i < 4; i++) {
    mbar_wait(bars, cur.full(), cur.phase);
    const uint32_t base = sm + cur.off();
    wg_fence();
#pragma unroll
    for (int ks = 0; ks < 8; ks++) {
      const uint64_t db = make_desc(base + (ks >> 2) * 6144 + (ks & 3) * 32, 16, 1024);
      if (i * 8 + ks < WREG) wgmma_n48(acc, wf[i * 8 + ks], db, (i > 0) || (ks > 0));
      else wgmma_n48_ss(acc, make_desc(ws + (i * 8 + ks - WREG) * 2048, 8192, 1024), db);
    }
    wg_commit();
    if (i > 0) {
      wg_wait<1>();
      if (leader) mbar_arrive(bars + prev_empty * 8);
    }
    prev_empty = cur.empty();
    cur.next();
  }
  wg_wait<0>();
  fence_regs(acc);
  if (leader) mbar_arrive(bars + prev_empty * 8);
}

__device__ __forceinline__ void epi_q(const float (&acc)[24], int br, int s, uint32_t sm) {
  const int tid = opaque_tid(), cta = opaque_cta();
  const int lane = tid & 31, w8 = (tid >> 5) - 4;
  const int h = cta >> 2, b = 4 * (cta & 3) + s;
  if (br == 1 && s == 0) {
    const uint32_t base = sm + SM_QS + (w8 >> 2) * 8192 + (lane >> 2) * 128 + (lane & 3) * 4;
    const int sw = lane >> 2, ch = (w8 & 3) * 2;
#pragma unroll
    for (int jb = 0; jb < 6; jb++) {
      const uint32_t lo = movmatrix_t(pack_bf16(acc[4 * jb + 0], acc[4 * jb + 1]));
      const uint32_t hi = movmatrix_t(pack_bf16(acc[4 * jb + 2], acc[4 * jb + 3]));
      asm volatile("st.shared.u32 [%0], %1;" ::"r"(base + jb * 1024 + ((ch ^ sw) << 4)), "r"(lo) : "memory");
      asm volatile("st.shared.u32 [%0], %1;" ::"r"(base + jb * 1024 + (((ch + 1) ^ sw) << 4)), "r"(hi) : "memory");
    }
    fence_proxy_async();
    return;
  }
  bf16* dst = br ? g_QB + (size_t)((b * NH + h) * SQ) * DH : g_QA + (size_t)((b * NGRP + (h >> 2)) * 192 + (h & 3) * SQ) * DH;
  const int q = lane & 3;
  bf16* p = dst + w8 * 16 + (lane >> 2) * 128 + q * 4;
  const int src = (lane & ~3) + (q & 1) * 2;
#pragma unroll
  for (int jb = 0; jb < 6; jb++) {
    const uint32_t lo = movmatrix_t(pack_bf16(acc[4 * jb + 0], acc[4 * jb + 1]));
    const uint32_t hi = movmatrix_t(pack_bf16(acc[4 * jb + 2], acc[4 * jb + 3]));
    const uint32_t l0 = __shfl_sync(0xffffffffu, lo, src), l1 = __shfl_sync(0xffffffffu, lo, src + 1);
    const uint32_t h0 = __shfl_sync(0xffffffffu, hi, src), h1 = __shfl_sync(0xffffffffu, hi, src + 1);
    *reinterpret_cast<uint2*>(p + jb * 8 * 128) = (q < 2) ? make_uint2(l0, l1) : make_uint2(h0, h1);
  }
}
__device__ __forceinline__ void epi_part(const float (&acc)[24], int br, int s) {
  const int tid = opaque_tid(), cta = opaque_cta();
  const int lane = tid & 31, w8 = (tid >> 5) - 4;
  const int h = cta >> 2, b = 4 * (cta & 3) + s;
  uint4* dst = g_part + ((size_t)(((br * NB + b) * 4 + (h & 3)) * 8 + w8)) * (8 * 96) + (h >> 2) * 96 + lane;
#pragma unroll
  for (int k = 0; k < 3; k++)
    dst[k * 32] = make_uint4(pack_bf16(acc[8 * k], acc[8 * k + 1]), pack_bf16(acc[8 * k + 2], acc[8 * k + 3]),
                             pack_bf16(acc[8 * k + 4], acc[8 * k + 5]), pack_bf16(acc[8 * k + 6], acc[8 * k + 7]));
}
__device__ __forceinline__ void finalize(uint32_t sm, uint32_t bars, GCur<1>& cur, bf16* out, int br, int q) {
  const int tid = opaque_tid(), cta = opaque_cta();
  const int t256 = tid - 128;
  const int h = cta >> 2;
  bf16* dst = out + (size_t)((4 * (cta & 3) + q) * SQ) * 1024 + br * 512 + (h & 3) * 128 + (h >> 2) * 16;
  mbar_wait(bars, cur.full(), cur.phase);
  const uint32_t b0 = sm + cur.off(); const int e0 = cur.empty(); cur.next();
  if (t256 < 192) {
    const int rp = t256 >> 3, c = (t256 & 7) * 2;
    const int wi = 2 * (rp >> 2) + (c >> 3);
    const uint32_t a0 = b0 + ((wi >> 2) * 32 + (c & 7) * 4 + (rp & 3)) * 16 + (wi & 3) * 4;
    float s00 = 0.f, s01 = 0.f, s10 = 0.f, s11 = 0.f;
#pragma unroll
    for (int p = 0; p < 8; p++) {
      uint32_t x0, x1;
      asm volatile("ld.shared.u32 %0, [%1];" : "=r"(x0) : "r"(a0 + p * 1536));
      asm volatile("ld.shared.u32 %0, [%1+64];" : "=r"(x1) : "r"(a0 + p * 1536));
      s00 += __uint_as_float(x0 << 16); s10 += __uint_as_float(x0 & 0xffff0000u);
      s01 += __uint_as_float(x1 << 16); s11 += __uint_as_float(x1 & 0xffff0000u);
    }
    *reinterpret_cast<uint32_t*>(dst + (2 * rp) * 1024 + c) = pack_bf16(s00, s01);
    *reinterpret_cast<uint32_t*>(dst + (2 * rp + 1) * 1024 + c) = pack_bf16(s10, s11);
  }
  __syncwarp();
  if ((tid & 31) == 0) mbar_arrive(bars + e0 * 8);
}

__device__ __forceinline__ void gemm_q0(uint32_t sm, uint32_t bars, GCur<0>& gc) {
  uint32_t wf[WREG][4];
  {
    GCur<2> wc; wc.init(0);
    load_w<2>(wf, sm, bars, wc);
  }
#pragma unroll 1
  for (int i = 0; i < PAD0; i++) {
    mbar_wait(bars, gc.full(), gc.phase);
    if ((opaque_tid() & 31) == 0) mbar_arrive(bars + gc.empty() * 8);
    gc.next();
  }
  mbar_wait(bars, B_WSF, 0);
#pragma unroll 1
  for (int s = 0; s < 2; s++) {
    float acc[24];
    brick<0>(acc, wf, sm, bars, gc);
    const bool leader = (opaque_tid() & 31) == 0;
    if (s == 1 && leader) mbar_arrive(bars + B_WSE * 8);
    epi_q(acc, 1, s, sm);
    __syncwarp();
    if (leader) mbar_arrive(bars + (s == 0 ? B_Q0 : B_EVG + 1) * 8);
    if (threadIdx.x == 128) TSTAMP(17 + s);
  }
}
__device__ __forceinline__ void gemm_q1(uint32_t sm, uint32_t bars, GCur<0>& gc) {
#pragma unroll 1
  for (int br = 0; br < 2; br++) {
    uint32_t wf[WREG][4];
    if (threadIdx.x == 128 && br == 0) TSTAMP(25);
    load_w<0>(wf, sm, bars, gc);
    mbar_wait(bars, B_WSF, (br + 1) & 1);
#pragma unroll 1
    for (int s = 2 * br; s < 4; s++) {
      float acc[24];
      brick<0>(acc, wf, sm, bars, gc);
      const bool leader = (opaque_tid() & 31) == 0;
      if (s == 3 && leader) mbar_arrive(bars + B_WSE * 8);
      epi_q(acc, br, s, sm);
      __syncwarp();
      if (leader) mbar_arrive(bars + (B_EVG + 2 + 2 * br + s) * 8);
      if (threadIdx.x == 128) TSTAMP(br ? 17 + s : 21 + s);
    }
  }
}
__device__ __forceinline__ void gemm_op(uint32_t sm, uint32_t bars, GCur<0>& gc, bf16* out) {
  GCur<1> xc; xc.init(0);
  {
    uint32_t wf[WREG][4];
    if (threadIdx.x == 128) TSTAMP(32);
    load_w<0>(wf, sm, bars, gc);
    mbar_wait(bars, B_WSF, 1);
#pragma unroll 1
    for (int s = 0; s < 4; s++) {
      float acc[24];
      brick<0>(acc, wf, sm, bars, gc);
      const bool leader = (opaque_tid() & 31) == 0;
      if (s == 3 && leader) mbar_arrive(bars + B_WSE * 8);
      epi_part(acc, 0, s);
      __syncwarp();
      if (leader) mbar_arrive(bars + (B_EVG + 8 + s) * 8);
      if (threadIdx.x == 128) TSTAMP(33 + s);
    }
  }
  {
    uint32_t wf[WREG][4];
    if (threadIdx.x == 128) TSTAMP(40);
    load_w<0>(wf, sm, bars, gc);
    mbar_wait(bars, B_WSF, 0);
#pragma unroll 1
    for (int s = 0; s < 4; s++) {
      float acc[24];
      brick<1>(acc, wf, sm, bars, xc);
      epi_part(acc, 1, s);
      __syncwarp();
      if ((opaque_tid() & 31) == 0) mbar_arrive(bars + (B_EVG + 12 + s) * 8);
      if (threadIdx.x == 128) TSTAMP(41 + s);
    }
  }
#pragma unroll 1
  for (int f = 0; f < 8; f++) finalize(sm, bars, xc, out, f >> 2, f & 3);
}
__global__ void __launch_bounds__(NTHREADS, 1) fused_kernel(const __grid_constant__ Params P) {
  extern __shared__ uint8_t smem_raw[];
  const uint32_t sm = (smem_u32(smem_raw) + 1023u) & ~1023u;
  const uint32_t bars = sm + SM_BAR;
  const int tid = threadIdx.x, wg = tid >> 7, warp = (tid >> 5) & 3, lane = tid & 31;
  const int cta = blockIdx.x;
  const int h = cta >> 2, j = cta & 3;
  const int n_t = h & 3, kc = h >> 2;

  if (tid == 0) {
    TSTAMP(0);
    asm volatile("st.shared.u32 [%0], %1;" ::"r"(bars + B_END * 8), "r"((uint32_t)clock()) : "memory");
  }
  if (tid < B_END) {
    int cnt = 1;
    if (tid >= B_KVE && tid < B_GF) cnt = 12;
    else if (tid >= B_GE && tid < B_EVA) cnt = 8;
    else if (tid >= B_EVA && tid < B_WSF) cnt = (tid == B_EVA + UA) ? 12 : 4;
    else if (tid == B_WSE || tid == B_WQE || tid == B_Q0) cnt = 8;
    else if (tid >= B_XE && tid < B_RDY) cnt = 8;
    mbar_init(bars + tid * 8, cnt);
    asm volatile("fence.mbarrier_init.release.cluster;" ::: "memory");
  }
  __syncthreads();

  if (wg == 3) {
    asm volatile("setmaxnreg.dec.sync.aligned.u32 32;");
    if (warp == 0 && lane == 0) {
      prefetch_tmap(&P.kB); prefetch_tmap(&P.vB); prefetch_tmap(&P.qB);
      prefetch_tmap(&P.kA); prefetch_tmap(&P.vA); prefetch_tmap(&P.qA);
      mbar_wait(bars, B_WQE, 0);
      const uint64_t pol = policy_evict_first();
      KCur c; c.init(0);
#pragma unroll 1
      for (int u = 0; u < 5; u++) {
        const bool isA = (u == UA);
        const int b = isA ? 4 * j + (h & 3) : 4 * j + (u < UA ? u : u - 1);
        const CUtensorMap* mk_ = isA ? &P.kA : &P.kB;
        const CUtensorMap* mv_ = isA ? &P.vA : &P.vB;
        const int row0 = isA ? (b * NGRP + kc) * SK : (b * NH + h) * SK;
        const int qslot = c.slot;
        if (u > 0) {
          mbar_wait(bars, B_KVE + c.slot, c.phase ^ 1);
          c.next();
        }
        bool qdone = (u == 0);
#pragma unroll 1
        for (int t = 0; t < 16; t++) {
          while (!qdone) {
            if (mbar_test(bars + (B_RDY + u) * 8, 0)) {
              mbar_expect_tx(bars + (B_KVF + qslot) * 8, SLOT);
              tma_3d(sm + SM_KV + qslot * SLOT, isA ? &P.qA : &P.qB, 0, isA ? (b * NGRP + kc) * 192 : (b * NH + h) * SQ, 0,
                     bars + (B_KVF + qslot) * 8);
              qdone = true;
              break;
            }
            if (mbar_test(bars + (B_KVE + c.slot) * 8, c.phase ^ 1)) break;
            if (expired(bars)) break;
            __nanosleep(64);
          }
          mbar_wait(bars, B_KVE + c.slot, c.phase ^ 1);
          mbar_expect_tx(bars + (B_KVF + c.slot) * 8, SLOT);
          tma_3d_hint(sm + SM_KV + c.slot * SLOT, (t & 1) ? mv_ : mk_, 0, row0 + (t >> 1) * 64, 0, bars + (B_KVF + c.slot) * 8, pol);
          c.next();
        }
      }
    } else if (warp == 1 && lane == 0) {
      prefetch_tmap(&P.wqB); prefetch_tmap(&P.wqBt); prefetch_tmap(&P.xB);
      GCur<0> c; c.init(0);
      uint32_t wsph = 1;
      auto ldWS = [&](const CUtensorMap* mt, int k0, int nch) {
        mbar_wait(bars, B_WSE, wsph);
        wsph ^= 1;
        mbar_expect_tx(bars + B_WSF * 8, (32 - WREG) * 4096);
        tma_3d(sm + SM_WS, mt, 0, k0 + WREG * 16, nch, bars + B_WSF * 8);
      };
      auto ldX = [&](const CUtensorMap* m, int row0, int ch0) {
#pragma unroll 1
        for (int i = 0; i < 4; i++) {
          mbar_wait(bars, c.empty(), c.phase ^ 1);
          mbar_expect_tx(bars + c.full() * 8, XBYTES);
          tma_3d(sm + c.off(), m, 0, row0, ch0 + 2 * i, bars + c.full() * 8);
          c.next();
        }
      };
      auto ldW = [&](const CUtensorMap* m, const CUtensorMap* mt, int k0, int nch) {
#pragma unroll 1
        for (int i = 0; i < WREG / 3; i++) {
          if (i == (NGS < WREG / 3 ? NGS : WREG / 3 - 1)) ldWS(mt, k0, nch);
          mbar_wait(bars, c.empty(), c.phase ^ 1);
          mbar_expect_tx(bars + c.full() * 8, XBYTES);
          tma_3d(sm + c.off(), m, 0, k0 + i * 48, nch, bars + c.full() * 8);
          c.next();
        }
      };
      {
        GCur<2> wc; wc.init(0);
#pragma unroll 1
        for (int i = 0; i < WREG / 3; i++) {
          mbar_expect_tx(bars + wc.full() * 8, XBYTES);
          tma_3d(sm + wc.off(), &P.wqB, 0, i * 48, 2 * h, bars + wc.full() * 8);
          wc.next();
        }
        ldWS(&P.wqBt, 0, 2 * h);
#pragma unroll 1
        for (int i = 0; i < PAD0; i++) { mbar_arrive(bars + c.full() * 8); c.next(); }
      }
#pragma unroll 1
      for (int s = 0; s < 2; s++) ldX(&P.xB, (4 * j + s) * SQ, 0);
      prefetch_tmap(&P.wqA); prefetch_tmap(&P.wqAt); prefetch_tmap(&P.xA);
      ldW(&P.wqA, &P.wqAt, 0, 2 * h);
#pragma unroll 1
      for (int s = 0; s < 4; s++) ldX(&P.xA, (4 * j + s) * SQ, 0);
      ldW(&P.wqB, &P.wqBt, 0, 2 * h);
#pragma unroll 1
      for (int s = 2; s < 4; s++) ldX(&P.xB, (4 * j + s) * SQ, 0);
      prefetch_tmap(&P.woA); prefetch_tmap(&P.oA); prefetch_tmap(&P.woB); prefetch_tmap(&P.oB);
      prefetch_tmap(&P.woAt); prefetch_tmap(&P.woBt);
#pragma unroll 1
      for (int i = 0; i < QPAD; i++) {
        mbar_wait(bars, c.empty(), c.phase ^ 1);
        mbar_arrive(bars + c.full() * 8);
        c.next();
      }
      {
        const int bA = 4 * j + (h & 3);
        mbar_wait(bars, B_RDY + UA, 0);
        GCur<0> c0 = c;
#pragma unroll 1
        for (int i = 0; i < 3; i++) { mbar_wait(bars, c.empty(), c.phase ^ 1); c.next(); }
        mbar_expect_tx(bars + c0.full() * 8, 32768);
        tma_3d(sm + c0.off(), &P.qA, 0, (bA * NGRP + kc) * 192 + 64, 0, bars + c0.full() * 8);
        tma_3d(sm + c0.off() + 16384, &P.qA, 0, (bA * NGRP + kc) * 192 + 128, 0, bars + c0.full() * 8);
        mbar_arrive(bars + (c0.full() + 1) * 8);
        mbar_arrive(bars + (c0.full() + 2) * 8);
      }
      ldW(&P.woA, &P.woAt, kc * 512, 2 * n_t);
#pragma unroll 1
      for (int s = 0; s < 4; s++) {
        mbar_wait(bars, B_RDY + 5 + s, 0);
#pragma unroll 1
        for (int i = 0; i < 4; i++) {
          mbar_wait(bars, c.empty(), c.phase ^ 1);
          mbar_expect_tx(bars + c.full() * 8, XBYTES);
          tma_3d(sm + c.off(), &P.oA, 0, ((4 * j + s) * NGRP + kc) * 192 + i * SQ, 0, bars + c.full() * 8);
          c.next();
        }
      }
      ldW(&P.woB, &P.woBt, kc * 512, 2 * n_t);
      {
#pragma unroll 1
        for (int i = 0; i < NGS; i++) { mbar_wait(bars, c.empty(), c.phase ^ 1); c.next(); }
        GCur<1> x; x.init(0);
        bool ext_ok = false;
        auto acquire = [&]() {
          if (x.slot >= NGS && !ext_ok) { mbar_wait(bars, B_EVA + 4, 0); ext_ok = true; }
          mbar_wait(bars, x.empty(), x.phase ^ 1);
        };
#pragma unroll 1
        for (int s = 0; s < 4; s++) {
          mbar_wait(bars, B_RDY + 9 + s, 0);
#pragma unroll 1
          for (int i = 0; i < 4; i++) {
            acquire();
            mbar_expect_tx(bars + x.full() * 8, XBYTES);
            tma_3d(sm + x.off(), &P.oB, 0, ((4 * j + s) * NH + 4 * kc + i) * SQ, 0, bars + x.full() * 8);
            x.next();
          }
        }
#pragma unroll 1
        for (int f = 0; f < 8; f++) {
          mbar_wait(bars, B_RDY + 13 + f, 0);
          const uint4* src = g_part + ((size_t)((((f >> 2) * NB + 4 * j + (f & 3)) * 4 + n_t) * 8 + kc)) * (8 * 96);
          acquire();
          mbar_expect_tx(bars + x.full() * 8, XBYTES);
          bulk_g2s(sm + x.off(), src, XBYTES, bars + x.full() * 8);
          x.next();
        }
      }
    } else if (warp == 2) {
      if (lane < 2) {
        const int nev = lane == 0 ? 16 : 5;
        int e = lane == 0 ? 1 : 0;
        while (e < nev) {
          if (mbar_test(bars + ((lane == 0 ? B_EVG : B_EVA) + e) * 8, 0)) {
            __threadfence();
            if (lane == 0 && (e == 1 || e == 6 || e == 7)) {
              const int s = e == 1 ? 1 : e - 4;
              fence_proxy_async_global();
              mbar_arrive(bars + (B_RDY + (s < UA ? s : s + 1)) * 8);
            } else {
              unsigned* f;
              if (lane == 0) {
                if (e < 8) f = &g_flags.qa_cnt[((4 * j + e - 2) * NGRP + kc) * 8];
                else f = &g_flags.part_cnt[(((e < 12 ? 0 : 1) * NB + 4 * j + (e & 3)) * 4 + n_t) * 8];
              } else {
                f = (e == UA) ? &g_flags.oa_cnt[((4 * j + (h & 3)) * NGRP + kc) * 8]
                              : &g_flags.ob_cnt[((4 * j + (e < UA ? e : e - 1)) * NGRP + kc) * 8];
              }
              red_add(f, 1);
            }
            e++;
          } else {
            if (expired(bars)) break;
            __nanosleep(POLL_NS);
          }
        }
      }
    } else if (warp == 3) {
      unsigned ep1 = 0;
      if (lane == 0) {
        const unsigned e = *reinterpret_cast<volatile unsigned*>(&g_flags.epoch);
        ep1 = e + 1;
        __threadfence();
        const unsigned old = atomicAdd(&g_flags.started, 1u);
        if (old == gridDim.x - 1) {
          g_flags.started = 0;
          __threadfence();
          *reinterpret_cast<volatile unsigned*>(&g_flags.epoch) = e + 1;
        }
      }
      ep1 = __shfl_sync(0xffffffffu, ep1, 0);
      const bool mine = (lane == UA) || (lane >= 5 && lane < 21);
      const unsigned* f = &g_flags.qa_cnt[((4 * j + (h & 3)) * NGRP + kc) * 8];
      unsigned target = 4 * ep1;
      if (lane >= 5 && lane < 9) { f = &g_flags.oa_cnt[((4 * j + lane - 5) * NGRP + kc) * 8]; target = ep1; }
      else if (lane >= 9 && lane < 13) { f = &g_flags.ob_cnt[((4 * j + lane - 9) * NGRP + kc) * 8]; target = 4 * ep1; }
      else if (lane >= 13 && lane < 21) { f = &g_flags.part_cnt[((((lane - 13) >> 2) * NB + 4 * j + ((lane - 13) & 3)) * 4 + n_t) * 8]; target = 8 * ep1; }
      bool done = !mine;
      while (true) {
        if (!done && (int)(ld_acquire(f) - target) >= 0) {
          fence_proxy_async_global();
          mbar_arrive(bars + (B_RDY + lane) * 8);
          done = true;
        }
        if (__all_sync(0xffffffffu, done)) break;
        if (__any_sync(0xffffffffu, expired(bars))) break;
        __nanosleep(POLL_NS);
      }
    }
  } else {
    asm volatile("setmaxnreg.inc.sync.aligned.u32 160;");
    GCur<0> gc; gc.init(0);
    uint32_t qs = sm + SM_QS;
    int qe0 = 0;
    if (wg != 0) {
      gemm_q0(sm, bars, gc);
      gemm_q1(sm, bars, gc);
      mbar_wait(bars, B_EVA + UA - 1, 0);
#pragma unroll 1
      for (int i = 0; i < QPAD; i++) {
        mbar_wait(bars, gc.full(), gc.phase);
        if (lane == 0) mbar_arrive(bars + gc.empty() * 8);
        gc.next();
      }
      qs = sm + gc.off() + (wg - 1) * 16384;
      qe0 = gc.empty();
#pragma unroll 1
      for (int i = 0; i < 3; i++) { mbar_wait(bars, gc.full(), gc.phase); gc.next(); }
    }
    {
      KCur cur; cur.init(wg == 0 ? 0 : KV_POS_A);
      const int u1 = wg == 0 ? 5 : UA + 1;
#pragma unroll 1
      for (int u = (wg == 0 ? 0 : UA); u < u1; u++) {
        if (tid == 0) TSTAMP(1 + 2 * u);
        attn_unit(sm, bars, cur, u, qs);
        if (tid == 0) TSTAMP(2 + 2 * u);
      }
    }
    if (wg != 0) {
      named_bar(5, 256);
      if (lane == 0) for (int i = 0; i < 3; i++) mbar_arrive(bars + (qe0 + i) * 8);
      gemm_op(sm, bars, gc, P.out);
      if (tid == 128) TSTAMP(48);
    }
  }
}

typedef CUresult (*EncodeFn)(CUtensorMap*, CUtensorMapDataType, cuuint32_t, void*, const cuuint64_t*, const cuuint64_t*,
                             const cuuint32_t*, const cuuint32_t*, CUtensorMapInterleave, CUtensorMapSwizzle,
                             CUtensorMapL2promotion, CUtensorMapFloatOOBfill);

static bool make_map(EncodeFn fn, CUtensorMap* m, const void* base, uint64_t rows, uint64_t row_elems, uint32_t box_rows) {
  cuuint64_t dims[3] = {64, rows, row_elems / 64};
  cuuint64_t strides[2] = {row_elems * 2, 128};
  cuuint32_t box[3] = {64, box_rows, 2};
  cuuint32_t estr[3] = {1, 1, 1};
  CUresult r = fn(m, CU_TENSOR_MAP_DATA_TYPE_BFLOAT16, 3, const_cast<void*>(base), dims, strides, box, estr,
                  CU_TENSOR_MAP_INTERLEAVE_NONE, CU_TENSOR_MAP_SWIZZLE_128B, CU_TENSOR_MAP_L2_PROMOTION_L2_256B,
                  CU_TENSOR_MAP_FLOAT_OOB_FILL_NONE);
  if (r != CUDA_SUCCESS) fprintf(stderr, "cuTensorMapEncodeTiled failed: %d\n", (int)r);
  return r == CUDA_SUCCESS;
}

}

extern "C" void kernel_launch(void* const* d_in, const int* in_sizes, int n_in, void* d_out, int out_size) {
  using namespace mk;
  static Params P;
  static bool init = false;
  static void* cached[11] = {0};
  bool same = init;
  for (int i = 0; i < 10; i++) same = same && (cached[i] == d_in[i]);
  same = same && (cached[10] == d_out);
  if (!same) {
    void* fnp = nullptr;
    cudaDriverEntryPointQueryResult qr;
    cudaGetDriverEntryPoint("cuTensorMapEncodeTiled", &fnp, cudaEnableDefault, &qr);
    EncodeFn fn = (EncodeFn)fnp;
    void *qa, *qb;
    cudaGetSymbolAddress(&qa, g_QA); cudaGetSymbolAddress(&qb, g_QB);
    make_map(fn, &P.xA, d_in[0], 768, 512, 48);
    make_map(fn, &P.kA, d_in[1], (uint64_t)NB * NGRP * SK, 128, 64);
    make_map(fn, &P.vA, d_in[2], (uint64_t)NB * NGRP * SK, 128, 64);
    make_map(fn, &P.wqA, d_in[3], 512, 4096, 48);
    make_map(fn, &P.wqAt, d_in[3], 512, 4096, (32 - WREG) * 16);
    make_map(fn, &P.woA, d_in[4], 4096, 512, 48);
    make_map(fn, &P.woAt, d_in[4], 4096, 512, (32 - WREG) * 16);
    make_map(fn, &P.xB, d_in[5], 768, 512, 48);
    make_map(fn, &P.kB, d_in[6], (uint64_t)NB * NH * SK, 128, 64);
    make_map(fn, &P.vB, d_in[7], (uint64_t)NB * NH * SK, 128, 64);
    make_map(fn, &P.wqB, d_in[8], 512, 4096, 48);
    make_map(fn, &P.wqBt, d_in[8], 512, 4096, (32 - WREG) * 16);
    make_map(fn, &P.woB, d_in[9], 4096, 512, 48);
    make_map(fn, &P.woBt, d_in[9], 4096, 512, (32 - WREG) * 16);
    make_map(fn, &P.qA, qa, (uint64_t)NB * NGRP * 192, 128, 64);
    make_map(fn, &P.qB, qb, (uint64_t)NB * NH * SQ + 16, 128, 64);
    make_map(fn, &P.oA, qa, (uint64_t)NB * NGRP * 192, 128, 48);
    make_map(fn, &P.oB, qb, (uint64_t)NB * NH * SQ + 16, 128, 48);
    P.out = (bf16*)d_out;
    cudaFuncSetAttribute(fused_kernel, cudaFuncAttributeMaxDynamicSharedMemorySize, SM_TOTAL);
    for (int i = 0; i < 10; i++) cached[i] = d_in[i];
    cached[10] = d_out;
    init = true;
  }
  fused_kernel<<<NCTA, NTHREADS, SM_TOTAL>>>(P);
}
```

```cpp
#include <cuda_runtime.h>
#include <cuda_bf16.h>
#include <cuda.h>
#include <stdint.h>
#include <stdio.h>
#include <stdlib.h>

namespace mk {

typedef __nv_bfloat16 bf16;

constexpr int NB = 16, SQ = 48, NH = 32, NGRP = 8, SK = 512, DH = 128;
constexpr int SLOT = 16384;
#define NKVS 4
#define NGS 10
#define POLL_NS 64
#define WAIT_HINT_NS 100000u
constexpr int XBYTES = 12288;
constexpr int WREG = 27;
constexpr int SM_QS = 0;
constexpr int SM_KV = 16384;
constexpr int SM_G = SM_KV + NKVS * SLOT;
constexpr int SM_WS = SM_G + NGS * XBYTES;
constexpr int SM_BAR = SM_WS + (32 - WREG) * 4096;
constexpr int SM_TOTAL = SM_BAR + 1024 + 1024;
constexpr int NEXT = (NKVS * SLOT) / XBYTES;
constexpr int NWIDE = NGS + NEXT;
constexpr int SM_EXT = SM_G - NEXT * XBYTES;
constexpr int PAD0 = NEXT >= WREG / 3 ? 0 : WREG / 3 - NEXT;
constexpr int QP_ENTRIES = PAD0 + 8 * 4 + 2 * (WREG / 3);
#define UA_POS 2
constexpr int UA = UA_POS;
constexpr int KV_POS_A = 16 + 17 * (UA - 1);
constexpr int QPAD = (QP_ENTRIES % NGS + 3 > NGS) ? NGS - QP_ENTRIES % NGS : 0;
constexpr int NCTA = 128;
constexpr int NTHREADS = 512;

constexpr int B_KVF = 0;
constexpr int B_KVE = B_KVF + NKVS;
constexpr int B_GF = B_KVE + NKVS;
constexpr int B_GE = B_GF + NGS;
constexpr int B_EVG = B_GE + NGS;
constexpr int B_EVA = B_EVG + 16;
constexpr int B_WSF = B_EVA + 5;
constexpr int B_WSE = B_WSF + 1;
constexpr int B_WQF = B_WSE + 1;
constexpr int B_WQE = B_WQF + WREG / 3;
constexpr int B_XF = B_WQE + 1;
constexpr int B_XE = B_XF + NWIDE;
constexpr int B_RDY = B_XE + NWIDE;
constexpr int B_Q0 = B_RDY + 21;
constexpr int B_END = B_Q0 + 1;
static_assert(B_END * 8 + 16 <= 1024 && B_END <= 512, "barrier region");
static_assert(SM_TOTAL <= 232448, "smem");

struct alignas(64) Params {
  CUtensorMap kA, vA, kB, vB, qA;
  CUtensorMap xA, xB;
  CUtensorMap oA, oB;
  CUtensorMap wqA, wqB, woA, woB;
  CUtensorMap wqAt, wqBt, woAt, woBt;
  bf16* out;
};

__device__ bf16 g_QA[NB * NGRP * 192 * DH];
__device__ bf16 g_QB[NB * NH * SQ * DH];
__device__ uint4 g_part[2 * NB * 4 * 8 * 8 * 96];
struct Flags {
  unsigned epoch;
  unsigned pad0[31];
  unsigned started;
  unsigned pad1[31];
  unsigned qa_cnt[NB * NGRP * 8];
  unsigned oa_cnt[NB * NGRP * 8];
  unsigned ob_cnt[NB * NGRP * 8];
  unsigned part_cnt[2 * NB * 4 * 8];
};
__device__ Flags g_flags;
__constant__ uint32_t c_zero;

#define TSTAMP(idx) do {} while (0)

__device__ __forceinline__ uint32_t smem_u32(const void* p) { return (uint32_t)__cvta_generic_to_shared(p); }
__device__ __forceinline__ void mbar_init(uint32_t bar, uint32_t cnt) {
  asm volatile("mbarrier.init.shared::cta.b64 [%0], %1;" ::"r"(bar), "r"(cnt) : "memory");
}
__device__ __forceinline__ void mbar_expect_tx(uint32_t bar, uint32_t bytes) {
  asm volatile("mbarrier.arrive.expect_tx.shared::cta.b64 _, [%0], %1;" ::"r"(bar), "r"(bytes) : "memory");
}
__device__ __forceinline__ void mbar_arrive(uint32_t bar) {
  asm volatile("mbarrier.arrive.shared::cta.b64 _, [%0];" ::"r"(bar) : "memory");
}
__device__ __forceinline__ void mbar_arrive_n(uint32_t bar, uint32_t n) {
  asm volatile("mbarrier.arrive.shared::cta.b64 _, [%0], %1;" ::"r"(bar), "r"(n) : "memory");
}
__device__ __forceinline__ bool mbar_try(uint32_t bar, uint32_t parity) {
  uint32_t ok;
  asm volatile("{\n.reg .pred p;\nmbarrier.try_wait.parity.shared::cta.b64 p, [%1], %2, %3;\nselp.u32 %0, 1, 0, p;\n}"
               : "=r"(ok) : "r"(bar), "r"(parity), "r"(WAIT_HINT_NS) : "memory");
  return ok != 0;
}
__device__ __forceinline__ bool mbar_test(uint32_t bar, uint32_t parity) {
  uint32_t ok;
  asm volatile("{\n.reg .pred p;\nmbarrier.test_wait.parity.shared::cta.b64 p, [%1], %2;\nselp.u32 %0, 1, 0, p;\n}"
               : "=r"(ok) : "r"(bar), "r"(parity) : "memory");
  return ok != 0;
}
__device__ __forceinline__ bool expired(uint32_t bars) {
  uint32_t t0, t1;
  asm volatile("ld.volatile.shared.u32 %0, [%1];" : "=r"(t0) : "r"(bars + B_END * 8));
  asm volatile("mov.u32 %0, %%clock;" : "=r"(t1));
  return (t1 - t0) > 1900000000u;
}
__device__ __forceinline__ int opaque_tid() {
  int t;
  asm volatile("mov.u32 %0, %%tid.x;" : "=r"(t));
  return t;
}
__device__ __forceinline__ int opaque_cta() {
  int t;
  asm volatile("mov.u32 %0, %%ctaid.x;" : "=r"(t));
  return t;
}
__device__ __forceinline__ void mbar_wait(uint32_t bars, int idx, uint32_t parity) {
  while (!mbar_try(bars + idx * 8, parity)) {
    if (expired(bars)) break;
  }
}
__device__ __forceinline__ unsigned ld_acquire(const unsigned* p) {
  unsigned v;
  asm volatile("ld.acquire.gpu.global.u32 %0, [%1];" : "=r"(v) : "l"(p) : "memory");
  return v;
}
__device__ __forceinline__ void red_add_release(unsigned* p, unsigned v) {
  asm volatile("red.release.gpu.global.add.u32 [%0], %1;" ::"l"(p), "r"(v) : "memory");
}
__device__ __forceinline__ void fence_acq_rel_gpu() { asm volatile("fence.acq_rel.gpu;" ::: "memory"); }
__device__ __forceinline__ void fence_proxy_async() { asm volatile("fence.proxy.async.shared::cta;" ::: "memory"); }
__device__ __forceinline__ void fence_proxy_async_global() { asm volatile("fence.proxy.async.global;" ::: "memory"); }
__device__ __forceinline__ void tma_3d(uint32_t dst, const CUtensorMap* map, int c0, int c1, int c2, uint32_t bar) {
  asm volatile(
      "cp.async.bulk.tensor.3d.shared::cluster.global.mbarrier::complete_tx::bytes [%0], [%1, {%3, %4, %5}], [%2];" ::"r"(dst),
      "l"(map), "r"(bar), "r"(c0), "r"(c1), "r"(c2)
      : "memory");
}
__device__ __forceinline__ void tma_3d_hint(uint32_t dst, const CUtensorMap* map, int c0, int c1, int c2, uint32_t bar, uint64_t pol) {
  asm volatile(
      "cp.async.bulk.tensor.3d.shared::cluster.global.mbarrier::complete_tx::bytes.L2::cache_hint [%0], [%1, {%3, %4, %5}], [%2], %6;" ::"r"(dst),
      "l"(map), "r"(bar), "r"(c0), "r"(c1), "r"(c2), "l"(pol)
      : "memory");
}
__device__ __forceinline__ uint64_t policy_evict_first() {
  uint64_t pol;
  asm volatile("createpolicy.fractional.L2::evict_first.b64 %0, 1.0;" : "=l"(pol));
  return pol;
}
__device__ __forceinline__ void bulk_g2s(uint32_t dst, const void* src, uint32_t bytes, uint32_t bar) {
  asm volatile("cp.async.bulk.shared::cluster.global.mbarrier::complete_tx::bytes [%0], [%1], %2, [%3];" ::"r"(dst), "l"(src),
               "r"(bytes), "r"(bar)
               : "memory");
}
__device__ __forceinline__ void prefetch_tmap(const CUtensorMap* map) {
  asm volatile("prefetch.tensormap [%0];" ::"l"(map) : "memory");
}
__device__ __forceinline__ void ldsm_x4_t(uint32_t (&r)[4], uint32_t addr) {
  asm volatile("ldmatrix.sync.aligned.m8n8.x4.trans.shared.b16 {%0,%1,%2,%3}, [%4];"
               : "=r"(r[0]), "=r"(r[1]), "=r"(r[2]), "=r"(r[3]) : "r"(addr) : "memory");
}
__device__ __forceinline__ void stsm_x4(uint32_t addr, uint32_t r0, uint32_t r1, uint32_t r2, uint32_t r3) {
  asm volatile("stmatrix.sync.aligned.m8n8.x4.shared.b16 [%0], {%1,%2,%3,%4};" ::"r"(addr), "r"(r0), "r"(r1), "r"(r2), "r"(r3)
               : "memory");
}
__device__ __forceinline__ uint4 lds128(uint32_t addr) {
  uint4 v;
  asm volatile("ld.shared.v4.u32 {%0,%1,%2,%3}, [%4];" : "=r"(v.x), "=r"(v.y), "=r"(v.z), "=r"(v.w) : "r"(addr) : "memory");
  return v;
}
__device__ __forceinline__ void sts128(uint32_t addr, uint4 v) {
  asm volatile("st.shared.v4.u32 [%0], {%1,%2,%3,%4};" ::"r"(addr), "r"(v.x), "r"(v.y), "r"(v.z), "r"(v.w) : "memory");
}
__device__ __forceinline__ uint32_t dep_on(uint32_t addr, uint32_t loaded) { return addr + (loaded & c_zero); }
__device__ __forceinline__ void named_bar(int id, int n) { asm volatile("bar.sync %0, %1;" ::"r"(id), "r"(n) : "memory"); }
__device__ __forceinline__ void wg_fence() { asm volatile("wgmma.fence.sync.aligned;" ::: "memory"); }
__device__ __forceinline__ void wg_commit() { asm volatile("wgmma.commit_group.sync.aligned;" ::: "memory"); }
template <int N>
__device__ __forceinline__ void wg_wait() { asm volatile("wgmma.wait_group.sync.aligned %0;" ::"n"(N) : "memory"); }
template <int N>
__device__ __forceinline__ void fence_regs(float (&a)[N]) {
#pragma unroll
  for (int i = 0; i < N; i++) asm volatile("" : "+f"(a[i])::"memory");
}
__device__ __forceinline__ uint64_t make_desc(uint32_t addr, uint32_t lbo, uint32_t sbo) {
  return (uint64_t)((addr & 0x3FFFF) >> 4) | ((uint64_t)(lbo >> 4) << 16) | ((uint64_t)(sbo >> 4) << 32) | (1ull << 62);
}
__device__ __forceinline__ uint32_t pack_bf16(float lo, float hi) {
  uint32_t r;
  asm("cvt.rn.bf16x2.f32 %0, %1, %2;" : "=r"(r) : "f"(hi), "f"(lo));
  return r;
}
__device__ __forceinline__ float ex2(float x) {
  float y;
  asm("ex2.approx.ftz.f32 %0, %1;" : "=f"(y) : "f"(x));
  return y;
}
__device__ __forceinline__ float rcp(float x) {
  float y;
  asm("rcp.approx.ftz.f32 %0, %1;" : "=f"(y) : "f"(x));
  return y;
}
__device__ __forceinline__ uint32_t movmatrix_t(uint32_t x) {
  uint32_t y;
  asm volatile("movmatrix.sync.aligned.m8n8.trans.b16 %0, %1;" : "=r"(y) : "r"(x));
  return y;
}

#define ACC8(d, o) "+f"(d[o]), "+f"(d[o + 1]), "+f"(d[o + 2]), "+f"(d[o + 3]), "+f"(d[o + 4]), "+f"(d[o + 5]), "+f"(d[o + 6]), "+f"(d[o + 7])
__device__ __forceinline__ void wgmma_n64_ss(float (&d)[32], uint64_t da, uint64_t db, int scale_d) {
  asm volatile(
      "{\n.reg .pred p;\nsetp.ne.b32 p, %34, 0;\n"
      "wgmma.mma_async.sync.aligned.m64n64k16.f32.bf16.bf16 "
      "{%0,%1,%2,%3,%4,%5,%6,%7,%8,%9,%10,%11,%12,%13,%14,%15,%16,%17,%18,%19,%20,%21,%22,%23,%24,%25,%26,%27,%28,%29,%30,%31},"
      "%32, %33, p, 1, 1, 0, 0;\n}"
      : ACC8(d, 0), ACC8(d, 8), ACC8(d, 16), ACC8(d, 24)
      : "l"(da), "l"(db), "r"(scale_d));
}
__device__ __forceinline__ void wgmma_n128_t(float (&d)[64], const uint32_t (&a)[4], uint64_t desc, int scale_d) {
  asm volatile(
      "{\n.reg .pred p;\nsetp.ne.b32 p, %69, 0;\n"
      "wgmma.mma_async.sync.aligned.m64n128k16.f32.bf16.bf16 "
      "{%0,%1,%2,%3,%4,%5,%6,%7,%8,%9,%10,%11,%12,%13,%14,%15,%16,%17,%18,%19,%20,%21,%22,%23,%24,%25,%26,%27,%28,%29,%30,%31,"
      "%32,%33,%34,%35,%36,%37,%38,%39,%40,%41,%42,%43,%44,%45,%46,%47,%48,%49,%50,%51,%52,%53,%54,%55,%56,%57,%58,%59,%60,%61,%62,%63},"
      "{%64,%65,%66,%67}, %68, p, 1, 1, 1;\n}"
      : ACC8(d, 0), ACC8(d, 8), ACC8(d, 16), ACC8(d, 24), ACC8(d, 32), ACC8(d, 40), ACC8(d, 48), ACC8(d, 56)
      : "r"(a[0]), "r"(a[1]), "r"(a[2]), "r"(a[3]), "l"(desc), "r"(scale_d));
}
__device__ __forceinline__ void wgmma_n48(float (&d)[24], const uint32_t (&a)[4], uint64_t desc, int scale_d) {
  asm volatile(
      "{\n.reg .pred p;\nsetp.ne.b32 p, %29, 0;\n"
      "wgmma.mma_async.sync.aligned.m64n48k16.f32.bf16.bf16 "
      "{%0,%1,%2,%3,%4,%5,%6,%7,%8,%9,%10,%11,%12,%13,%14,%15,%16,%17,%18,%19,%20,%21,%22,%23},"
      "{%24,%25,%26,%27}, %28, p, 1, 1, 0;\n}"
      : ACC8(d, 0), ACC8(d, 8), ACC8(d, 16)
      : "r"(a[0]), "r"(a[1]), "r"(a[2]), "r"(a[3]), "l"(desc), "r"(scale_d));
}
__device__ __forceinline__ void wgmma_n48_ss(float (&d)[24], uint64_t descA, uint64_t descB) {
  asm volatile(
      "{\n.reg .pred p;\nsetp.ne.b32 p, 1, 0;\n"
      "wgmma.mma_async.sync.aligned.m64n48k16.f32.bf16.bf16 "
      "{%0,%1,%2,%3,%4,%5,%6,%7,%8,%9,%10,%11,%12,%13,%14,%15,%16,%17,%18,%19,%20,%21,%22,%23},"
      "%24, %25, p, 1, 1, 1, 0;\n}"
      : ACC8(d, 0), ACC8(d, 8), ACC8(d, 16)
      : "l"(descA), "l"(descB));
}

struct KCur {
  int slot;
  uint32_t phase;
  __device__ __forceinline__ void init(int count) { slot = count % NKVS; phase = (count / NKVS) & 1; }
  __device__ __forceinline__ void next() { if (++slot == NKVS) { slot = 0; phase ^= 1; } }
};
template <int MODE>
struct GCur {
  int slot;
  uint32_t phase;
  static constexpr int N = MODE == 0 ? NGS : (MODE == 1 ? NWIDE : WREG / 3);
  __device__ __forceinline__ void init(int count) { slot = count % N; phase = (count / N) & 1; }
  __device__ __forceinline__ void next() { if (++slot == N) { slot = 0; phase ^= 1; } }
  __device__ __forceinline__ uint32_t off() const {
    if (MODE == 0) return SM_G + slot * XBYTES;
    if (MODE == 1) return SM_EXT + (slot < NGS ? slot + NEXT : slot - NGS) * XBYTES;
    return SM_EXT + slot * XBYTES;
  }
  __device__ __forceinline__ int full() const { return (MODE == 0 ? B_GF : (MODE == 1 ? B_XF : B_WQF)) + slot; }
  __device__ __forceinline__ int empty() const { return MODE == 2 ? B_WQE : (MODE == 0 ? B_GE : B_XE) + slot; }
};

constexpr float SM_C = 0.08838834764831845f * 1.4426950408889634f;
constexpr float RESCALE_T = 8.0f;

__device__ __forceinline__ void softmax_step(const float (&s)[32], uint32_t (&pf)[4][4], float (&o)[64], float& m0, float& m1,
                                             float& l0, float& l1, bool first) {
  float mx0 = fmaxf(s[0], s[1]), mx1 = fmaxf(s[2], s[3]);
#pragma unroll
  for (int j = 1; j < 8; j++) {
    mx0 = fmaxf(mx0, fmaxf(s[4 * j], s[4 * j + 1]));
    mx1 = fmaxf(mx1, fmaxf(s[4 * j + 2], s[4 * j + 3]));
  }
  mx0 = fmaxf(mx0, __shfl_xor_sync(0xffffffffu, mx0, 1));
  mx1 = fmaxf(mx1, __shfl_xor_sync(0xffffffffu, mx1, 1));
  mx0 = fmaxf(mx0, __shfl_xor_sync(0xffffffffu, mx0, 2));
  mx1 = fmaxf(mx1, __shfl_xor_sync(0xffffffffu, mx1, 2));
  const bool grow = !((mx0 - m0) * SM_C <= RESCALE_T) || !((mx1 - m1) * SM_C <= RESCALE_T);
  if (__any_sync(0xffffffffu, grow)) {
    const float mn0 = fmaxf(m0, mx0), mn1 = fmaxf(m1, mx1);
    const float a0 = ex2((m0 - mn0) * SM_C), a1 = ex2((m1 - mn1) * SM_C);
    m0 = mn0; m1 = mn1;
    l0 *= a0; l1 *= a1;
    if (!first) {
#pragma unroll
      for (int j = 0; j < 16; j++) {
        o[4 * j] *= a0; o[4 * j + 1] *= a0; o[4 * j + 2] *= a1; o[4 * j + 3] *= a1;
      }
    }
  }
  const float mc0 = m0 * SM_C, mc1 = m1 * SM_C;
#pragma unroll
  for (int j = 0; j < 8; j++) {
    const float p0 = ex2(fmaf(s[4 * j], SM_C, -mc0)), p1 = ex2(fmaf(s[4 * j + 1], SM_C, -mc0));
    const float p2 = ex2(fmaf(s[4 * j + 2], SM_C, -mc1)), p3 = ex2(fmaf(s[4 * j + 3], SM_C, -mc1));
    l0 += p0 + p1; l1 += p2 + p3;
    pf[j >> 1][(j & 1) * 2 + 0] = pack_bf16(p0, p1);
    pf[j >> 1][(j & 1) * 2 + 1] = pack_bf16(p2, p3);
  }
}

__device__ __forceinline__ void attn_unit(uint32_t sm, uint32_t bars, KCur& cur, int u, uint32_t qs) {
  const int tid_ = opaque_tid();
  const bool leader = (tid_ & 31) == 0;
  const bool isA = (u == UA);
  const uint32_t narr = isA ? 1 : 3;
  const bool active = isA || (tid_ >> 5) < 3;
  if (u == 0) {
    mbar_wait(bars, B_Q0, 0);
  } else {
    mbar_wait(bars, B_KVF + cur.slot, cur.phase);
    uint32_t rel = bars + (B_KVE + cur.slot) * 8;
    if (tid_ < 128) {
      named_bar(1, 128);
      const uint32_t src = sm + SM_KV + cur.slot * SLOT + tid_ * 16, dst = qs + tid_ * 16;
      const uint32_t hstride = isA ? 8192 : 6144;
      uint32_t x = 0;
#pragma unroll
      for (int i = 0; i < 8; i++) {
        if (isA || (i & 3) < 3) {
          const uint4 v = lds128(src + (i >> 2) * hstride + (i & 3) * 2048);
          sts128(dst + i * 2048, v);
          x ^= v.x;
        }
      }
      rel = dep_on(rel, x);
      fence_proxy_async();
      named_bar(1, 128);
    }
    if (leader) mbar_arrive_n(rel, narr);
    cur.next();
  }
  float o[64];
  float s[32];
  float m0 = -INFINITY, m1 = -INFINITY, l0 = 0.f, l1 = 0.f;
  mbar_wait(bars, B_KVF + cur.slot, cur.phase);
  wg_fence();
#pragma unroll
  for (int ks = 0; ks < 8; ks++)
    wgmma_n64_ss(s, make_desc(qs + (ks >> 2) * 8192 + (ks & 3) * 32, 16, 1024),
                 make_desc(sm + SM_KV + cur.slot * SLOT + (ks >> 2) * 8192 + (ks & 3) * 32, 16, 1024), ks > 0);
  wg_commit();
  wg_wait<0>();
  fence_regs(s);
  if (leader) mbar_arrive_n(bars + (B_KVE + cur.slot) * 8, narr);
  cur.next();
#pragma unroll 1
  for (int t = 0; t < 8; t++) {
    uint32_t pf[4][4];
    if (active) softmax_step(s, pf, o, m0, m1, l0, l1, t == 0);
    else {
#pragma unroll
      for (int k = 0; k < 4; k++) { pf[k][0] = 0; pf[k][1] = 0; pf[k][2] = 0; pf[k][3] = 0; }
    }
    const int vs = cur.slot; const uint32_t vp = cur.phase; cur.next();
    mbar_wait(bars, B_KVF + vs, vp);
    wg_fence();
#pragma unroll
    for (int kk = 0; kk < 4; kk++)
      wgmma_n128_t(o, pf[kk], make_desc(sm + SM_KV + vs * SLOT + kk * 2048, 8192, 1024), (t > 0) || (kk > 0));
    wg_commit();
    if (t < 7) {
      const int ks_ = cur.slot;
      mbar_wait(bars, B_KVF + ks_, cur.phase);
      cur.next();
      wg_fence();
#pragma unroll
      for (int ks = 0; ks < 8; ks++)
        wgmma_n64_ss(s, make_desc(qs + (ks >> 2) * 8192 + (ks & 3) * 32, 16, 1024),
                     make_desc(sm + SM_KV + ks_ * SLOT + (ks >> 2) * 8192 + (ks & 3) * 32, 16, 1024), ks > 0);
      wg_commit();
      wg_wait<1>();
      if (leader) mbar_arrive_n(bars + (B_KVE + vs) * 8, narr);
      wg_wait<0>();
      if (leader) mbar_arrive_n(bars + (B_KVE + ks_) * 8, narr);
    } else {
      wg_wait<0>();
      if (leader) mbar_arrive_n(bars + (B_KVE + vs) * 8, narr);
    }
    fence_regs(s); fence_regs(o);
  }
  if (active) {
    l0 += __shfl_xor_sync(0xffffffffu, l0, 1); l1 += __shfl_xor_sync(0xffffffffu, l1, 1);
    l0 += __shfl_xor_sync(0xffffffffu, l0, 2); l1 += __shfl_xor_sync(0xffffffffu, l1, 2);
    const float i0 = rcp(l0), i1 = rcp(l1);
    const int tid = opaque_tid(), cta = opaque_cta();
    const int lane = tid & 31, w4 = (tid >> 5) & 3;
    named_bar(2 + (tid >> 7), isA ? 128 : 96);
    const uint32_t stg = qs + w4 * 4096;
    {
      const int mi = lane >> 3, row = (mi & 1) * 8 + (lane & 7);
#pragma unroll
      for (int jp = 0; jp < 8; jp++) {
        const int chunk = 2 * jp + (mi >> 1);
        stsm_x4(stg + row * 256 + ((chunk ^ (row & 7)) << 4), pack_bf16(o[8 * jp] * i0, o[8 * jp + 1] * i0),
                pack_bf16(o[8 * jp + 2] * i1, o[8 * jp + 3] * i1), pack_bf16(o[8 * jp + 4] * i0, o[8 * jp + 5] * i0),
                pack_bf16(o[8 * jp + 6] * i1, o[8 * jp + 7] * i1));
      }
    }
    __syncwarp();
    const int h = cta >> 2, jg = cta & 3;
    const int r0 = (tid >> 5) * 16;
    bf16* orow = isA ? g_QA + (size_t)(((4 * jg + (h & 3)) * NGRP + (h >> 2)) * 192 + r0) * DH
                     : g_QB + (size_t)(((4 * jg + (u < UA ? u : u - 1)) * NH + h) * SQ + r0) * DH;
#pragma unroll 2
    for (int i = 0; i < 8; i++) {
      const int row = 2 * i + (lane >> 4), chunk = lane & 15;
      const uint4 v = lds128(stg + row * 256 + ((chunk ^ (row & 7)) << 4));
      *reinterpret_cast<uint4*>(orow + row * DH + chunk * 8) = v;
    }
  }
  __syncwarp();
  if ((opaque_tid() & 31) == 0) mbar_arrive(bars + (B_EVA + u) * 8);
}

template <int MODE>
__device__ __forceinline__ uint32_t load_w(uint32_t (&wf)[WREG][4], uint32_t sm, uint32_t bars, GCur<MODE>& cur) {
  const int tid = opaque_tid();
  const int lane = tid & 31, warp = (tid >> 5) & 3, half = (tid >> 7) - 1;
  const int mi = lane >> 3, rr = lane & 7;
  const int chunk = warp * 2 + (mi & 1);
  const uint32_t off = sm + half * 6144 + ((mi >> 1) * 8 + rr) * 128 + ((chunk ^ rr) << 4);
  uint32_t all = 0;
#pragma unroll
  for (int c = 0; c < WREG / 3; c++) {
    mbar_wait(bars, cur.full(), cur.phase);
    const uint32_t base = off + cur.off();
#pragma unroll
    for (int ks = 0; ks < 3; ks++) ldsm_x4_t(wf[c * 3 + ks], base + ks * 2048);
    const uint32_t x = wf[c * 3][0] ^ wf[c * 3 + 1][0] ^ wf[c * 3 + 2][0];
    if (MODE == 2) {
      all ^= x;
      if (c == (NEXT < WREG / 3 ? NEXT : WREG / 3) - 1) {
        const uint32_t rel = dep_on(bars + B_WQE * 8, all);
        __syncwarp();
        if (lane == 0) mbar_arrive(rel);
      }
    } else {
      const uint32_t rel = dep_on(bars + cur.empty() * 8, x);
      __syncwarp();
      if (lane == 0) mbar_arrive(rel);
    }
    cur.next();
  }
  return all;
}

template <int MODE>
__device__ __forceinline__ void brick(float (&acc)[24], const uint32_t (&wf)[WREG][4], uint32_t sm, uint32_t bars, GCur<MODE>& cur) {
  int prev_empty = 0;
  const int tid = opaque_tid();
  const bool leader = (tid & 31) == 0;
  const uint32_t ws = sm + SM_WS + ((tid >> 7) - 1) * ((32 - WREG) * 2048);
#pragma unroll
  for (int i = 0; i < 4; i++) {
    mbar_wait(bars, cur.full(), cur.phase);
    const uint32_t base = sm + cur.off();
    wg_fence();
#pragma unroll
    for (int ks = 0; ks < 8; ks++) {
      const uint64_t db = make_desc(base + (ks >> 2) * 6144 + (ks & 3) * 32, 16, 1024);
      if (i * 8 + ks < WREG) wgmma_n48(acc, wf[i * 8 + ks], db, (i > 0) || (ks > 0));
      else wgmma_n48_ss(acc, make_desc(ws + (i * 8 + ks - WREG) * 2048, 8192, 1024), db);
    }
    wg_commit();
    if (i > 0) {
      wg_wait<1>();
      if (leader) mbar_arrive(bars + prev_empty * 8);
    }
    prev_empty = cur.empty();
    cur.next();
  }
  wg_wait<0>();
  fence_regs(acc);
  if (leader) mbar_arrive(bars + prev_empty * 8);
}

__device__ __forceinline__ void epi_q(const float (&acc)[24], int br, int s, uint32_t sm) {
  const int tid = opaque_tid(), cta = opaque_cta();
  const int lane = tid & 31, w8 = (tid >> 5) - 4;
  const int h = cta >> 2, b = 4 * (cta & 3) + s;
  if (br == 1 && s == 0) {
    const uint32_t base = sm + SM_QS + (w8 >> 2) * 8192 + (lane >> 2) * 128 + (lane & 3) * 4;
    const int sw = lane >> 2, ch = (w8 & 3) * 2;
#pragma unroll
    for (int jb = 0; jb < 6; jb++) {
      const uint32_t lo = movmatrix_t(pack_bf16(acc[4 * jb + 0], acc[4 * jb + 1]));
      const uint32_t hi = movmatrix_t(pack_bf16(acc[4 * jb + 2], acc[4 * jb + 3]));
      asm volatile("st.shared.u32 [%0], %1;" ::"r"(base + jb * 1024 + ((ch ^ sw) << 4)), "r"(lo) : "memory");
      asm volatile("st.shared.u32 [%0], %1;" ::"r"(base + jb * 1024 + (((ch + 1) ^ sw) << 4)), "r"(hi) : "memory");
    }
    fence_proxy_async();
    return;
  }
  bf16* dst = br ? g_QB + (size_t)((b * NH + h) * SQ) * DH : g_QA + (size_t)((b * NGRP + (h >> 2)) * 192 + (h & 3) * SQ) * DH;
  const int q = lane & 3;
  bf16* p = dst + w8 * 16 + (lane >> 2) * 128 + q * 4;
  const int src = (lane & ~3) + (q & 1) * 2;
#pragma unroll
  for (int jb = 0; jb < 6; jb++) {
    const uint32_t lo = movmatrix_t(pack_bf16(acc[4 * jb + 0], acc[4 * jb + 1]));
    const uint32_t hi = movmatrix_t(pack_bf16(acc[4 * jb + 2], acc[4 * jb + 3]));
    const uint32_t l0 = __shfl_sync(0xffffffffu, lo, src), l1 = __shfl_sync(0xffffffffu, lo, src + 1);
    const uint32_t h0 = __shfl_sync(0xffffffffu, hi, src), h1 = __shfl_sync(0xffffffffu, hi, src + 1);
    *reinterpret_cast<uint2*>(p + jb * 8 * 128) = (q < 2) ? make_uint2(l0, l1) : make_uint2(h0, h1);
  }
}
__device__ __forceinline__ void epi_part(const float (&acc)[24], int br, int s) {
  const int tid = opaque_tid(), cta = opaque_cta();
  const int lane = tid & 31, w8 = (tid >> 5) - 4;
  const int h = cta >> 2, b = 4 * (cta & 3) + s;
  uint4* dst = g_part + ((size_t)(((br * NB + b) * 4 + (h & 3)) * 8 + w8)) * (8 * 96) + (h >> 2) * 96 + lane;
#pragma unroll
  for (int k = 0; k < 3; k++)
    dst[k * 32] = make_uint4(pack_bf16(acc[8 * k], acc[8 * k + 1]), pack_bf16(acc[8 * k + 2], acc[8 * k + 3]),
                             pack_bf16(acc[8 * k + 4], acc[8 * k + 5]), pack_bf16(acc[8 * k + 6], acc[8 * k + 7]));
}
__device__ __forceinline__ void finalize(uint32_t sm, uint32_t bars, GCur<1>& cur, bf16* out, int br, int q) {
  const int tid = opaque_tid(), cta = opaque_cta();
  const int t256 = tid - 128;
  const int h = cta >> 2;
  bf16* dst = out + (size_t)((4 * (cta & 3) + q) * SQ) * 1024 + br * 512 + (h & 3) * 128 + (h >> 2) * 16;
  mbar_wait(bars, cur.full(), cur.phase);
  const uint32_t b0 = sm + cur.off(); const int e0 = cur.empty(); cur.next();
  if (t256 < 192) {
    const int rp = t256 >> 3, c = (t256 & 7) * 2;
    const int wi = 2 * (rp >> 2) + (c >> 3);
    const uint32_t a0 = b0 + ((wi >> 2) * 32 + (c & 7) * 4 + (rp & 3)) * 16 + (wi & 3) * 4;
    float s00 = 0.f, s01 = 0.f, s10 = 0.f, s11 = 0.f;
#pragma unroll
    for (int p = 0; p < 8; p++) {
      uint32_t x0, x1;
      asm volatile("ld.shared.u32 %0, [%1];" : "=r"(x0) : "r"(a0 + p * 1536));
      asm volatile("ld.shared.u32 %0, [%1+64];" : "=r"(x1) : "r"(a0 + p * 1536));
      s00 += __uint_as_float(x0 << 16); s10 += __uint_as_float(x0 & 0xffff0000u);
      s01 += __uint_as_float(x1 << 16); s11 += __uint_as_float(x1 & 0xffff0000u);
    }
    *reinterpret_cast<uint32_t*>(dst + (2 * rp) * 1024 + c) = pack_bf16(s00, s01);
    *reinterpret_cast<uint32_t*>(dst + (2 * rp + 1) * 1024 + c) = pack_bf16(s10, s11);
  }
  __syncwarp();
  if ((tid & 31) == 0) mbar_arrive(bars + e0 * 8);
}

__device__ __forceinline__ void gemm_q0(uint32_t sm, uint32_t bars, GCur<0>& gc) {
  uint32_t wf[WREG][4];
  uint32_t all;
  {
    GCur<2> wc; wc.init(0);
    all = load_w<2>(wf, sm, bars, wc);
  }
#pragma unroll 1
  for (int i = 0; i < PAD0; i++) {
    mbar_wait(bars, gc.full(), gc.phase);
    const uint32_t rel = dep_on(bars + gc.empty() * 8, all);
    __syncwarp();
    if ((opaque_tid() & 31) == 0) mbar_arrive(rel);
    gc.next();
  }
  mbar_wait(bars, B_WSF, 0);
#pragma unroll 1
  for (int s = 0; s < 2; s++) {
    float acc[24];
    brick<0>(acc, wf, sm, bars, gc);
    const bool leader = (opaque_tid() & 31) == 0;
    if (s == 1 && leader) mbar_arrive(bars + B_WSE * 8);
    epi_q(acc, 1, s, sm);
    __syncwarp();
    if (leader) mbar_arrive(bars + (s == 0 ? B_Q0 : B_EVG + 1) * 8);
    if (threadIdx.x == 128) TSTAMP(17 + s);
  }
}
__device__ __forceinline__ void gemm_q1(uint32_t sm, uint32_t bars, GCur<0>& gc) {
#pragma unroll 1
  for (int br = 0; br < 2; br++) {
    uint32_t wf[WREG][4];
    if (threadIdx.x == 128 && br == 0) TSTAMP(25);
    load_w<0>(wf, sm, bars, gc);
    mbar_wait(bars, B_WSF, (br + 1) & 1);
#pragma unroll 1
    for (int s = 2 * br; s < 4; s++) {
      float acc[24];
      brick<0>(acc, wf, sm, bars, gc);
      const bool leader = (opaque_tid() & 31) == 0;
      if (s == 3 && leader) mbar_arrive(bars + B_WSE * 8);
      epi_q(acc, br, s, sm);
      __syncwarp();
      if (leader) mbar_arrive(bars + (B_EVG + 2 + 2 * br + s) * 8);
      if (threadIdx.x == 128) TSTAMP(br ? 17 + s : 21 + s);
    }
  }
}
__device__ __forceinline__ void gemm_op(uint32_t sm, uint32_t bars, GCur<0>& gc, bf16* out) {
  GCur<1> xc; xc.init(0);
  {
    uint32_t wf[WREG][4];
    if (threadIdx.x == 128) TSTAMP(32);
    load_w<0>(wf, sm, bars, gc);
    mbar_wait(bars, B_WSF, 1);
#pragma unroll 1
    for (int s = 0; s < 4; s++) {
      float acc[24];
      brick<0>(acc, wf, sm, bars, gc);
      const bool leader = (opaque_tid() & 31) == 0;
      if (s == 3 && leader) mbar_arrive(bars + B_WSE * 8);
      epi_part(acc, 0, s);
      __syncwarp();
      if (leader) mbar_arrive(bars + (B_EVG + 8 + s) * 8);
      if (threadIdx.x == 128) TSTAMP(33 + s);
    }
  }
  {
    uint32_t wf[WREG][4];
    if (threadIdx.x == 128) TSTAMP(40);
    load_w<0>(wf, sm, bars, gc);
    mbar_wait(bars, B_WSF, 0);
#pragma unroll 1
    for (int s = 0; s < 4; s++) {
      float acc[24];
      brick<1>(acc, wf, sm, bars, xc);
      epi_part(acc, 1, s);
      __syncwarp();
      if ((opaque_tid() & 31) == 0) mbar_arrive(bars + (B_EVG + 12 + s) * 8);
      if (threadIdx.x == 128) TSTAMP(41 + s);
    }
  }
#pragma unroll 1
  for (int f = 0; f < 8; f++) finalize(sm, bars, xc, out, f >> 2, f & 3);
}
__global__ void __launch_bounds__(NTHREADS, 1) fused_kernel(const __grid_constant__ Params P) {
  extern __shared__ uint8_t smem_raw[];
  const uint32_t sm = (smem_u32(smem_raw) + 1023u) & ~1023u;
  const uint32_t bars = sm + SM_BAR;
  const int tid = threadIdx.x, wg = tid >> 7, warp = (tid >> 5) & 3, lane = tid & 31;
  const int cta = blockIdx.x;
  const int h = cta >> 2, j = cta & 3;
  const int n_t = h & 3, kc = h >> 2;

  if (tid == 0) {
    TSTAMP(0);
    asm volatile("st.shared.u32 [%0], %1;" ::"r"(bars + B_END * 8), "r"((uint32_t)clock()) : "memory");
  }
  if (tid == 416) {
    prefetch_tmap(&P.wqB); prefetch_tmap(&P.wqBt); prefetch_tmap(&P.xB);
    for (int i = 0; i < WREG / 3; i++) mbar_init(bars + (B_WQF + i) * 8, 1);
    for (int i = 0; i < NGS; i++) mbar_init(bars + (B_GF + i) * 8, 1);
    mbar_init(bars + B_WSF * 8, 1);
    asm volatile("fence.mbarrier_init.release.cluster;" ::: "memory");
    fence_proxy_async();
    GCur<2> wc; wc.init(0);
#pragma unroll 1
    for (int i = 0; i < WREG / 3; i++) {
      mbar_expect_tx(bars + wc.full() * 8, XBYTES);
      tma_3d(sm + wc.off(), &P.wqB, 0, i * 48, 2 * h, bars + wc.full() * 8);
      wc.next();
    }
    mbar_expect_tx(bars + B_WSF * 8, (32 - WREG) * 4096);
    tma_3d(sm + SM_WS, &P.wqBt, 0, WREG * 16, 2 * h, bars + B_WSF * 8);
#pragma unroll 1
    for (int i = 0; i < NGS - PAD0 && i < 8; i++) {
      mbar_expect_tx(bars + (B_GF + PAD0 + i) * 8, XBYTES);
      tma_3d(sm + SM_G + (PAD0 + i) * XBYTES, &P.xB, 0, (4 * j + (i >> 2)) * SQ, 2 * (i & 3), bars + (B_GF + PAD0 + i) * 8);
    }
  }
  if (tid < B_END && tid != B_WSF && !(tid >= B_WQF && tid < B_WQF + WREG / 3) && !(tid >= B_GF && tid < B_GF + NGS)) {
    int cnt = 1;
    if (tid >= B_KVE && tid < B_GF) cnt = 12;
    else if (tid >= B_GE && tid < B_EVA) cnt = 8;
    else if (tid >= B_EVA && tid < B_WSF) cnt = (tid == B_EVA + UA) ? 12 : 4;
    else if (tid == B_WSE || tid == B_WQE || tid == B_Q0) cnt = 8;
    else if (tid >= B_XE && tid < B_RDY) cnt = 8;
    mbar_init(bars + tid * 8, cnt);
    asm volatile("fence.mbarrier_init.release.cluster;" ::: "memory");
  }
  __syncthreads();

  if (wg == 3) {
    asm volatile("setmaxnreg.dec.sync.aligned.u32 32;");
    if (warp == 0 && lane == 0) {
      prefetch_tmap(&P.kB); prefetch_tmap(&P.vB); prefetch_tmap(&P.oB);
      prefetch_tmap(&P.kA); prefetch_tmap(&P.vA); prefetch_tmap(&P.qA);
      mbar_wait(bars, B_WQE, 0);
      const uint64_t pol = policy_evict_first();
      KCur c; c.init(0);
#pragma unroll 1
      for (int u = 0; u < 5; u++) {
        const bool isA = (u == UA);
        const int b = isA ? 4 * j + (h & 3) : 4 * j + (u < UA ? u : u - 1);
        const CUtensorMap* mk_ = isA ? &P.kA : &P.kB;
        const CUtensorMap* mv_ = isA ? &P.vA : &P.vB;
        const int row0 = isA ? (b * NGRP + kc) * SK : (b * NH + h) * SK;
        const int qslot = c.slot;
        if (u > 0) {
          mbar_wait(bars, B_KVE + c.slot, c.phase ^ 1);
          c.next();
        }
        bool qdone = (u == 0);
#pragma unroll 1
        for (int t = 0; t < 16; t++) {
          while (!qdone) {
            if (mbar_test(bars + (B_RDY + u) * 8, 0)) {
              mbar_expect_tx(bars + (B_KVF + qslot) * 8, isA ? SLOT : XBYTES);
              tma_3d(sm + SM_KV + qslot * SLOT, isA ? &P.qA : &P.oB, 0, isA ? (b * NGRP + kc) * 192 : (b * NH + h) * SQ, 0,
                     bars + (B_KVF + qslot) * 8);
              qdone = true;
              break;
            }
            if (mbar_test(bars + (B_KVE + c.slot) * 8, c.phase ^ 1)) break;
            if (expired(bars)) break;
            __nanosleep(64);
          }
          mbar_wait(bars, B_KVE + c.slot, c.phase ^ 1);
          mbar_expect_tx(bars + (B_KVF + c.slot) * 8, SLOT);
          tma_3d_hint(sm + SM_KV + c.slot * SLOT, (t & 1) ? mv_ : mk_, 0, row0 + (t >> 1) * 64, 0, bars + (B_KVF + c.slot) * 8, pol);
          c.next();
        }
      }
    } else if (warp == 1 && lane == 0) {
      GCur<0> c; c.init(0);
      uint32_t wsph = 1;
      auto ldWS = [&](const CUtensorMap* mt, int k0, int nch) {
        mbar_wait(bars, B_WSE, wsph);
        wsph ^= 1;
        mbar_expect_tx(bars + B_WSF * 8, (32 - WREG) * 4096);
        tma_3d(sm + SM_WS, mt, 0, k0 + WREG * 16, nch, bars + B_WSF * 8);
      };
      auto ldX = [&](const CUtensorMap* m, int row0, int ch0) {
#pragma unroll 1
        for (int i = 0; i < 4; i++) {
          mbar_wait(bars, c.empty(), c.phase ^ 1);
          mbar_expect_tx(bars + c.full() * 8, XBYTES);
          tma_3d(sm + c.off(), m, 0, row0, ch0 + 2 * i, bars + c.full() * 8);
          c.next();
        }
      };
      auto ldW = [&](const CUtensorMap* m, const CUtensorMap* mt, int k0, int nch) {
#pragma unroll 1
        for (int i = 0; i < WREG / 3; i++) {
          if (i == (NGS < WREG / 3 ? NGS : WREG / 3 - 1)) ldWS(mt, k0, nch);
          mbar_wait(bars, c.empty(), c.phase ^ 1);
          mbar_expect_tx(bars + c.full() * 8, XBYTES);
          tma_3d(sm + c.off(), m, 0, k0 + i * 48, nch, bars + c.full() * 8);
          c.next();
        }
      };
      wsph = 0;
#pragma unroll 1
      for (int i = 0; i < PAD0; i++) { mbar_arrive(bars + c.full() * 8); c.next(); }
      constexpr int XPRE = (NGS - PAD0 < 8) ? NGS - PAD0 : 8;
#pragma unroll 1
      for (int i = 0; i < XPRE; i++) c.next();
#pragma unroll 1
      for (int i = XPRE; i < 8; i++) {
        mbar_wait(bars, c.empty(), c.phase ^ 1);
        mbar_expect_tx(bars + c.full() * 8, XBYTES);
        tma_3d(sm + c.off(), &P.xB, 0, (4 * j + (i >> 2)) * SQ, 2 * (i & 3), bars + c.full() * 8);
        c.next();
      }
      prefetch_tmap(&P.wqA); prefetch_tmap(&P.wqAt); prefetch_tmap(&P.xA);
      ldW(&P.wqA, &P.wqAt, 0, 2 * h);
#pragma unroll 1
      for (int s = 0; s < 4; s++) ldX(&P.xA, (4 * j + s) * SQ, 0);
      ldW(&P.wqB, &P.wqBt, 0, 2 * h);
#pragma unroll 1
      for (int s = 2; s < 4; s++) ldX(&P.xB, (4 * j + s) * SQ, 0);
      prefetch_tmap(&P.woA); prefetch_tmap(&P.oA); prefetch_tmap(&P.woB); prefetch_tmap(&P.oB);
      prefetch_tmap(&P.woAt); prefetch_tmap(&P.woBt);
#pragma unroll 1
      for (int i = 0; i < QPAD; i++) {
        mbar_wait(bars, c.empty(), c.phase ^ 1);
        mbar_arrive(bars + c.full() * 8);
        c.next();
      }
      {
        const int bA = 4 * j + (h & 3);
        mbar_wait(bars, B_RDY + UA, 0);
        GCur<0> c0 = c;
#pragma unroll 1
        for (int i = 0; i < 3; i++) { mbar_wait(bars, c.empty(), c.phase ^ 1); c.next(); }
        mbar_expect_tx(bars + c0.full() * 8, 32768);
        tma_3d(sm + c0.off(), &P.qA, 0, (bA * NGRP + kc) * 192 + 64, 0, bars + c0.full() * 8);
        tma_3d(sm + c0.off() + 16384, &P.qA, 0, (bA * NGRP + kc) * 192 + 128, 0, bars + c0.full() * 8);
        mbar_arrive(bars + (c0.full() + 1) * 8);
        mbar_arrive(bars + (c0.full() + 2) * 8);
      }
      ldW(&P.woA, &P.woAt, kc * 512, 2 * n_t);
#pragma unroll 1
      for (int s = 0; s < 4; s++) {
        mbar_wait(bars, B_RDY + 5 + s, 0);
#pragma unroll 1
        for (int i = 0; i < 4; i++) {
          mbar_wait(bars, c.empty(), c.phase ^ 1);
          mbar_expect_tx(bars + c.full() * 8, XBYTES);
          tma_3d(sm + c.off(), &P.oA, 0, ((4 * j + s) * NGRP + kc) * 192 + i * SQ, 0, bars + c.full() * 8);
          c.next();
        }
      }
      ldW(&P.woB, &P.woBt, kc * 512, 2 * n_t);
      {
#pragma unroll 1
        for (int i = 0; i < NGS; i++) { mbar_wait(bars, c.empty(), c.phase ^ 1); c.next(); }
        GCur<1> x; x.init(0);
        bool ext_ok = false;
        auto acquire = [&]() {
          if (x.slot >= NGS && !ext_ok) { mbar_wait(bars, B_EVA + 4, 0); ext_ok = true; }
          mbar_wait(bars, x.empty(), x.phase ^ 1);
        };
#pragma unroll 1
        for (int s = 0; s < 4; s++) {
          mbar_wait(bars, B_RDY + 9 + s, 0);
#pragma unroll 1
          for (int i = 0; i < 4; i++) {
            acquire();
            mbar_expect_tx(bars + x.full() * 8, XBYTES);
            tma_3d(sm + x.off(), &P.oB, 0, ((4 * j + s) * NH + 4 * kc + i) * SQ, 0, bars + x.full() * 8);
            x.next();
          }
        }
#pragma unroll 1
        for (int f = 0; f < 8; f++) {
          mbar_wait(bars, B_RDY + 13 + f, 0);
          const uint4* src = g_part + ((size_t)((((f >> 2) * NB + 4 * j + (f & 3)) * 4 + n_t) * 8 + kc)) * (8 * 96);
          acquire();
          mbar_expect_tx(bars + x.full() * 8, XBYTES);
          bulk_g2s(sm + x.off(), src, XBYTES, bars + x.full() * 8);
          x.next();
        }
      }
    } else if (warp == 2) {
      if (lane < 2) {
        const int nev = lane == 0 ? 16 : 5;
        int e = lane == 0 ? 1 : 0;
        while (e < nev) {
          if (mbar_test(bars + ((lane == 0 ? B_EVG : B_EVA) + e) * 8, 0)) {
            if (lane == 0 && (e == 1 || e == 6 || e == 7)) {
              const int s = e == 1 ? 1 : e - 4;
              fence_acq_rel_gpu();
              fence_proxy_async_global();
              mbar_arrive(bars + (B_RDY + (s < UA ? s : s + 1)) * 8);
            } else {
              unsigned* f;
              if (lane == 0) {
                if (e < 8) f = &g_flags.qa_cnt[((4 * j + e - 2) * NGRP + kc) * 8];
                else f = &g_flags.part_cnt[(((e < 12 ? 0 : 1) * NB + 4 * j + (e & 3)) * 4 + n_t) * 8];
              } else {
                f = (e == UA) ? &g_flags.oa_cnt[((4 * j + (h & 3)) * NGRP + kc) * 8]
                              : &g_flags.ob_cnt[((4 * j + (e < UA ? e : e - 1)) * NGRP + kc) * 8];
              }
              red_add_release(f, 1);
            }
            e++;
          } else {
            if (expired(bars)) break;
            __nanosleep(POLL_NS);
          }
        }
      }
    } else if (warp == 3) {
      unsigned ep1 = 0;
      if (lane == 0) {
        const unsigned e = *reinterpret_cast<volatile unsigned*>(&g_flags.epoch);
        ep1 = e + 1;
        __threadfence();
        const unsigned old = atomicAdd(&g_flags.started, 1u);
        if (old == gridDim.x - 1) {
          g_flags.started = 0;
          __threadfence();
          *reinterpret_cast<volatile unsigned*>(&g_flags.epoch) = e + 1;
        }
      }
      ep1 = __shfl_sync(0xffffffffu, ep1, 0);
      const bool mine = (lane == UA) || (lane >= 5 && lane < 21);
      const unsigned* f = &g_flags.qa_cnt[((4 * j + (h & 3)) * NGRP + kc) * 8];
      unsigned target = 4 * ep1;
      if (lane >= 5 && lane < 9) { f = &g_flags.oa_cnt[((4 * j + lane - 5) * NGRP + kc) * 8]; target = ep1; }
      else if (lane >= 9 && lane < 13) { f = &g_flags.ob_cnt[((4 * j + lane - 9) * NGRP + kc) * 8]; target = 4 * ep1; }
      else if (lane >= 13 && lane < 21) { f = &g_flags.part_cnt[((((lane - 13) >> 2) * NB + 4 * j + ((lane - 13) & 3)) * 4 + n_t) * 8]; target = 8 * ep1; }
      bool done = !mine;
      while (true) {
        if (!done && (int)(ld_acquire(f) - target) >= 0) {
          fence_proxy_async_global();
          mbar_arrive(bars + (B_RDY + lane) * 8);
          done = true;
        }
        if (__all_sync(0xffffffffu, done)) break;
        if (__any_sync(0xffffffffu, expired(bars))) break;
        __nanosleep(POLL_NS);
      }
    }
  } else {
    asm volatile("setmaxnreg.inc.sync.aligned.u32 160;");
    GCur<0> gc; gc.init(0);
    uint32_t qs = sm + SM_QS;
    int qe0 = 0;
    if (wg != 0) {
      gemm_q0(sm, bars, gc);
      gemm_q1(sm, bars, gc);
      mbar_wait(bars, B_EVA + UA - 1, 0);
#pragma unroll 1
      for (int i = 0; i < QPAD; i++) {
        mbar_wait(bars, gc.full(), gc.phase);
        if (lane == 0) mbar_arrive(bars + gc.empty() * 8);
        gc.next();
      }
      qs = sm + gc.off() + (wg - 1) * 16384;
      qe0 = gc.empty();
#pragma unroll 1
      for (int i = 0; i < 3; i++) { mbar_wait(bars, gc.full(), gc.phase); gc.next(); }
    }
    {
      KCur cur; cur.init(wg == 0 ? 0 : KV_POS_A);
      const int u1 = wg == 0 ? 5 : UA + 1;
#pragma unroll 1
      for (int u = (wg == 0 ? 0 : UA); u < u1; u++) {
        if (tid == 0) TSTAMP(1 + 2 * u);
        attn_unit(sm, bars, cur, u, qs);
        if (tid == 0) TSTAMP(2 + 2 * u);
      }
    }
    if (wg != 0) {
      named_bar(5, 256);
      if (lane == 0) for (int i = 0; i < 3; i++) mbar_arrive(bars + (qe0 + i) * 8);
      gemm_op(sm, bars, gc, P.out);
      if (tid == 128) TSTAMP(48);
    }
  }
}

typedef CUresult (*EncodeFn)(CUtensorMap*, CUtensorMapDataType, cuuint32_t, void*, const cuuint64_t*, const cuuint64_t*,
                             const cuuint32_t*, const cuuint32_t*, CUtensorMapInterleave, CUtensorMapSwizzle,
                             CUtensorMapL2promotion, CUtensorMapFloatOOBfill);

static bool make_map(EncodeFn fn, CUtensorMap* m, const void* base, uint64_t rows, uint64_t row_elems, uint32_t box_rows) {
  cuuint64_t dims[3] = {64, rows, row_elems / 64};
  cuuint64_t strides[2] = {row_elems * 2, 128};
  cuuint32_t box[3] = {64, box_rows, 2};
  cuuint32_t estr[3] = {1, 1, 1};
  CUresult r = fn(m, CU_TENSOR_MAP_DATA_TYPE_BFLOAT16, 3, const_cast<void*>(base), dims, strides, box, estr,
                  CU_TENSOR_MAP_INTERLEAVE_NONE, CU_TENSOR_MAP_SWIZZLE_128B, CU_TENSOR_MAP_L2_PROMOTION_L2_256B,
                  CU_TENSOR_MAP_FLOAT_OOB_FILL_NONE);
  if (r != CUDA_SUCCESS) fprintf(stderr, "cuTensorMapEncodeTiled failed: %d\n", (int)r);
  return r == CUDA_SUCCESS;
}

}

extern "C" void kernel_launch(void* const* d_in, const int* in_sizes, int n_in, void* d_out, int out_size) {
  using namespace mk;
  static Params P;
  static bool init = false;
  static void* cached[11] = {0};
  bool same = init;
  for (int i = 0; i < 10; i++) same = same && (cached[i] == d_in[i]);
  same = same && (cached[10] == d_out);
  if (!same) {
    void* fnp = nullptr;
    cudaDriverEntryPointQueryResult qr;
    cudaGetDriverEntryPoint("cuTensorMapEncodeTiled", &fnp, cudaEnableDefault, &qr);
    EncodeFn fn = (EncodeFn)fnp;
    void *qa, *qb;
    cudaGetSymbolAddress(&qa, g_QA); cudaGetSymbolAddress(&qb, g_QB);
    make_map(fn, &P.xA, d_in[0], 768, 512, 48);
    make_map(fn, &P.kA, d_in[1], (uint64_t)NB * NGRP * SK, 128, 64);
    make_map(fn, &P.vA, d_in[2], (uint64_t)NB * NGRP * SK, 128, 64);
    make_map(fn, &P.wqA, d_in[3], 512, 4096, 48);
    make_map(fn, &P.wqAt, d_in[3], 512, 4096, (32 - WREG) * 16);
    make_map(fn, &P.woA, d_in[4], 4096, 512, 48);
    make_map(fn, &P.woAt, d_in[4], 4096, 512, (32 - WREG) * 16);
    make_map(fn, &P.xB, d_in[5], 768, 512, 48);
    make_map(fn, &P.kB, d_in[6], (uint64_t)NB * NH * SK, 128, 64);
    make_map(fn, &P.vB, d_in[7], (uint64_t)NB * NH * SK, 128, 64);
    make_map(fn, &P.wqB, d_in[8], 512, 4096, 48);
    make_map(fn, &P.wqBt, d_in[8], 512, 4096, (32 - WREG) * 16);
    make_map(fn, &P.woB, d_in[9], 4096, 512, 48);
    make_map(fn, &P.woBt, d_in[9], 4096, 512, (32 - WREG) * 16);
    make_map(fn, &P.qA, qa, (uint64_t)NB * NGRP * 192, 128, 64);
    make_map(fn, &P.oA, qa, (uint64_t)NB * NGRP * 192, 128, 48);
    make_map(fn, &P.oB, qb, (uint64_t)NB * NH * SQ, 128, 48);
    P.out = (bf16*)d_out;
    cudaFuncSetAttribute(fused_kernel, cudaFuncAttributeMaxDynamicSharedMemorySize, SM_TOTAL);
    for (int i = 0; i < 10; i++) cached[i] = d_in[i];
    cached[10] = d_out;
    init = true;
  }
  fused_kernel<<<NCTA, NTHREADS, SM_TOTAL>>>(P);
}
```
